```python
import torch

def _softmax(x, axis=-1):
    return torch.softmax(x, dim=axis)
def _gelu(x):
    return torch.nn.functional.gelu(x, approximate="tanh")
def _silu(x):
    return torch.nn.functional.silu(x)
def _sigmoid(x):
    return torch.sigmoid(x)
def _layernorm(x, axis=-1, eps=1e-5):
    m = x.mean(dim=axis, keepdim=True)
    v = x.var(dim=axis, keepdim=True, unbiased=False)
    return (x - m) / torch.sqrt(v + eps)
def _scatter_add(tgt, idx, src, axis=0):
    return tgt.clone().index_add_(axis, idx, src)
def _segment_sum(src, seg, n):
    out = torch.zeros((n,) + src.shape[1:], dtype=src.dtype)
    return out.index_add_(0, seg, src)
def _pad(x, pw):
    flat = tuple(v for pair in reversed(pw) for v in pair)
    return torch.nn.functional.pad(x, flat)

kernel_name = 'gated_mix__mha_block_cached__glu_gated_glu__decode'

def setup_inputs():

    _w = (lambda a: (lambda t: t.to(torch.bfloat16) if t.is_floating_point() else t)(torch.as_tensor(a)))
    def _A_setup():
        B, Sq, D = 2, 1, 448
        H, Sk, Dh = 16, 8192, 256
        return {
            "x": _w((lambda *s: torch.randn(*s, dtype=torch.bfloat16) * 0.05)(B, Sq, D)),
            "k_cache": _w((lambda *s: torch.randn(*s, dtype=torch.bfloat16) * 6.4)(B, H, Sk, Dh)),
            "v_cache": _w((lambda *s: torch.randn(*s, dtype=torch.bfloat16) * 0.4)(B, H, Sk, Dh)),
            "wq": _w((lambda *s: torch.randn(*s, dtype=torch.bfloat16) * 6.4)(D, H * Dh) * (D ** -0.5)),
            "wo": _w((lambda *s: torch.randn(*s, dtype=torch.bfloat16) * 0.4)(H * Dh, D) * ((H * Dh) ** -0.5)),
        }
    _A_in = _A_setup()

    def _B_setup():
        B, S, D, F = 2, 1, 448, 1792
        return {
            "x": _w((lambda *s: torch.randn(*s, dtype=torch.bfloat16) * 0.05)(B, S, D)),
            "w_gate": _w((lambda *s: torch.randn(*s, dtype=torch.bfloat16) * 0.4)(D, F)),
            "w_up": _w((lambda *s: torch.randn(*s, dtype=torch.bfloat16) * 0.05)(D, F)),
            "w_down": _w((lambda *s: torch.randn(*s, dtype=torch.bfloat16) * 0.05)(F, D)),
        }
    _B_in = _B_setup()

    return {
        "A_x": _A_in["x"],
        "A_k_cache": _A_in["k_cache"],
        "A_v_cache": _A_in["v_cache"],
        "A_wq": _A_in["wq"],
        "A_wo": _A_in["wo"],
        "B_x": _B_in["x"],
        "B_w_gate": _B_in["w_gate"],
        "B_w_up": _B_in["w_up"],
        "B_w_down": _B_in["w_down"],
        "gate_w": _w((lambda *s: torch.randn(*s, dtype=torch.bfloat16) * 0.05)(448) * 16.0),
    }

def reference(A_x, A_k_cache, A_v_cache, A_wq, A_wo, B_x, B_w_gate, B_w_up, B_w_down, gate_w):
    def _A_ref(x, k_cache, v_cache, wq, wo):
        B, Sq, D = x.shape
        H, Dh = 16, 256
        q = (lambda x, *d: x.permute(*d))((x @ wq).reshape(B, Sq, H, Dh), 0, 2, 1, 3)
        scores = torch.einsum("bhqd,bhkd->bhqk", q, k_cache) * (Dh ** -0.5)
        p = _softmax(scores, axis=-1)
        o = torch.einsum("bhqk,bhkd->bhqd", p, v_cache)
        return (lambda x, *d: x.permute(*d))(o, 0, 2, 1, 3).reshape(B, Sq, H * Dh) @ wo

    def _B_ref(x, w_gate, w_up, w_down):
        g = torch.einsum("bsd,df->bsf", x, w_gate)
        u = torch.einsum("bsd,df->bsf", x, w_up)
        h = _sigmoid(g) * u
        return torch.einsum("bsf,fd->bsd", h, w_down)

    x = A_x
    g = _sigmoid((x * gate_w).sum(-1, keepdims=True))
    a = _A_ref(x, A_k_cache, A_v_cache, A_wq, A_wo)
    b = _B_ref(x, B_w_gate, B_w_up, B_w_down)
    return g * a + (1 - g) * b
```

```cpp
#include <cuda_runtime.h>
#include <cuda_bf16.h>
#include <stdint.h>

namespace {

constexpr int kD = 448;
constexpr int kH = 16;
constexpr int kSK = 8192;
constexpr int kDH = 256;
constexpr int kF = 1792;
constexpr int kHD = kH * kDH;

constexpr int NW = 8;
constexpr int NT = NW * 32;
constexpr int STAGES = 4;
constexpr int KPS = 8;
constexpr int SB = KPS * kDH * 2;
constexpr int GW = 4 * NW;
constexpr int NCH = kSK / KPS / GW;
constexpr int KPW = NCH * KPS;
constexpr int N_ATT = 128;
constexpr int N_GLU = 4;
constexpr int WO_WARP_BYTES = 8 * kD * 2;

constexpr int SM_RING = 0;
constexpr int SM_WO = SM_RING + NW * STAGES * SB;
constexpr int SM_SC = SM_WO + NW * WO_WARP_BYTES;
constexpr int SM_Q = SM_SC + NW * KPW * 4;
constexpr int SM_QP = SM_Q + kDH * 4;
constexpr int SM_BAR = SM_QP + NW * 64 * 4;
constexpr int SM_TOTAL = SM_BAR + NW * (STAGES + 1) * 8;
static_assert(SM_TOTAL <= 232448, "smem");

constexpr unsigned SPIN_LIMIT = 1u << 22;

__device__ unsigned int g_qbox[N_ATT][4][64];
__device__ uint2 g_mlbox[N_ATT][GW];
__device__ unsigned int g_obox[N_ATT][4][64];
__device__ __align__(32) unsigned int g_outbox[N_ATT][64 + N_GLU][8];

__device__ __forceinline__ uint32_t smem_u32(const void* p) { return (uint32_t)__cvta_generic_to_shared(p); }
__device__ __forceinline__ void mbar_init(uint32_t bar, uint32_t cnt) {
    asm volatile("mbarrier.init.shared::cta.b64 [%0], %1;" ::"r"(bar), "r"(cnt) : "memory");
}
__device__ __forceinline__ void mbar_expect_tx(uint32_t bar, uint32_t bytes) {
    asm volatile("mbarrier.arrive.expect_tx.shared::cta.b64 _, [%0], %1;" ::"r"(bar), "r"(bytes) : "memory");
}
__device__ __forceinline__ bool mbar_try_wait(uint32_t bar, uint32_t parity) {
    uint32_t ok;
    asm volatile(
        "{\n .reg .pred p;\n mbarrier.try_wait.parity.shared::cta.b64 p, [%1], %2;\n selp.u32 %0, 1, 0, p;\n }"
        : "=r"(ok)
        : "r"(bar), "r"(parity)
        : "memory");
    return ok != 0;
}
__device__ __forceinline__ void mbar_wait(uint32_t bar, uint32_t parity) {
    unsigned n = 0;
    while (!mbar_try_wait(bar, parity)) {
        if (++n > SPIN_LIMIT) __trap();
    }
}
__device__ __forceinline__ void bulk_g2s(uint32_t dst, const void* src, uint32_t bytes, uint32_t bar) {
    asm volatile("cp.async.bulk.shared::cluster.global.mbarrier::complete_tx::bytes [%0], [%1], %2, [%3];" ::"r"(dst),
                 "l"(src), "r"(bytes), "r"(bar)
                 : "memory");
}
__device__ __forceinline__ uint4 lds128(uint32_t a) {
    uint4 v;
    asm volatile("ld.shared.v4.u32 {%0,%1,%2,%3}, [%4];" : "=r"(v.x), "=r"(v.y), "=r"(v.z), "=r"(v.w) : "r"(a) : "memory");
    return v;
}
__device__ __forceinline__ uint32_t lds32(uint32_t a) {
    uint32_t v;
    asm volatile("ld.shared.u32 %0, [%1];" : "=r"(v) : "r"(a) : "memory");
    return v;
}
__device__ __forceinline__ float ldsf(uint32_t a) { return __uint_as_float(lds32(a)); }
__device__ __forceinline__ void stsf(uint32_t a, float v) { asm volatile("st.shared.f32 [%0], %1;" ::"r"(a), "f"(v) : "memory"); }
__device__ __forceinline__ void sts64f(uint32_t a, float x, float y) {
    asm volatile("st.shared.v2.f32 [%0], {%1,%2};" ::"r"(a), "f"(x), "f"(y) : "memory");
}
__device__ __forceinline__ void sts128f(uint32_t a, float x, float y, float z, float w) {
    asm volatile("st.shared.v4.f32 [%0], {%1,%2,%3,%4};" ::"r"(a), "f"(x), "f"(y), "f"(z), "f"(w) : "memory");
}
__device__ __forceinline__ uint4 ldg_nc128(const void* p) {
    uint4 v;
    asm volatile("ld.global.nc.L1::no_allocate.v4.u32 {%0,%1,%2,%3}, [%4];" : "=r"(v.x), "=r"(v.y), "=r"(v.z), "=r"(v.w) : "l"(p));
    return v;
}
__device__ __forceinline__ uint32_t ldg_nc32(const void* p) {
    uint32_t v;
    asm volatile("ld.global.nc.u32 %0, [%1];" : "=r"(v) : "l"(p));
    return v;
}
__device__ __forceinline__ void box_st32(void* p, uint32_t v) { asm volatile("st.relaxed.gpu.global.u32 [%0], %1;" ::"l"(p), "r"(v) : "memory"); }
__device__ __forceinline__ void box_st64(void* p, uint32_t x, uint32_t y) {
    asm volatile("st.relaxed.gpu.global.v2.u32 [%0], {%1,%2};" ::"l"(p), "r"(x), "r"(y) : "memory");
}
__device__ __forceinline__ void box_st128(void* p, uint32_t x, uint32_t y, uint32_t z, uint32_t w) {
    asm volatile("st.relaxed.gpu.global.v4.u32 [%0], {%1,%2,%3,%4};" ::"l"(p), "r"(x), "r"(y), "r"(z), "r"(w) : "memory");
}
__device__ __forceinline__ uint32_t box_ld32(const void* p) {
    uint32_t v;
    asm volatile("ld.relaxed.gpu.global.u32 %0, [%1];" : "=r"(v) : "l"(p) : "memory");
    return v;
}
__device__ __forceinline__ uint2 box_ld64(const void* p) {
    uint2 v;
    asm volatile("ld.relaxed.gpu.global.v2.u32 {%0,%1}, [%2];" : "=r"(v.x), "=r"(v.y) : "l"(p) : "memory");
    return v;
}
__device__ __forceinline__ uint4 box_ld128(const void* p) {
    uint4 v;
    asm volatile("ld.relaxed.gpu.global.v4.u32 {%0,%1,%2,%3}, [%4];" : "=r"(v.x), "=r"(v.y), "=r"(v.z), "=r"(v.w) : "l"(p) : "memory");
    return v;
}
__device__ __forceinline__ uint32_t box_enc(float f) {
    uint32_t u = __float_as_uint(f);
    return u == 0u ? 0x80000000u : u;
}
__device__ __forceinline__ float box_poll32(unsigned int* p) {
    uint32_t v;
    unsigned n = 0;
    while ((v = box_ld32(p)) == 0u) {
        if (++n > SPIN_LIMIT) __trap();
    }
    box_st32(p, 0u);
    return __uint_as_float(v);
}
__device__ __forceinline__ float bflo(uint32_t u) { return __uint_as_float(u << 16); }
__device__ __forceinline__ float bfhi(uint32_t u) { return __uint_as_float(u & 0xffff0000u); }
__device__ __forceinline__ float bfr(float f) { return __bfloat162float(__float2bfloat16_rn(f)); }
__device__ __forceinline__ float sigmoidf_(float v) { return 1.0f / (1.0f + __expf(-v)); }
__device__ __forceinline__ void cta_sync() { asm volatile("bar.sync 0;" ::: "memory"); }

__device__ __forceinline__ void glu_cta(unsigned char* smem, int j, const __nv_bfloat16* __restrict__ x,
                                        const __nv_bfloat16* __restrict__ wg, const __nv_bfloat16* __restrict__ wu,
                                        const __nv_bfloat16* __restrict__ wd) {
    float* xs = reinterpret_cast<float*>(smem);
    float* hs = xs + 2 * kD;
    float* red = hs + 2 * kD;
    const int t = threadIdx.x;
    for (int i = t; i < 2 * kD; i += NT) xs[i] = __bfloat162float(x[i]);
    cta_sync();
    const int cc = t % 56, rg = t / 56;
    constexpr int U = 8;
    if (t < 224) {
        float ag[2][8], au[2][8];
#pragma unroll
        for (int e = 0; e < 8; e++) ag[0][e] = ag[1][e] = au[0][e] = au[1][e] = 0.f;
        const __nv_bfloat16* pg = wg + (size_t)rg * kF + j * 448 + cc * 8;
        const __nv_bfloat16* pu = wu + (size_t)rg * kF + j * 448 + cc * 8;
        for (int i0 = 0; i0 < 112; i0 += U) {
            uint4 a[U], b[U];
#pragma unroll
            for (int u = 0; u < U; u++) {
                a[u] = ldg_nc128(pg + (size_t)(i0 + u) * 4 * kF);
                b[u] = ldg_nc128(pu + (size_t)(i0 + u) * 4 * kF);
            }
#pragma unroll
            for (int u = 0; u < U; u++) {
                const int row = rg + (i0 + u) * 4;
                const float x0 = xs[row], x1 = xs[kD + row];
                const uint32_t wa[4] = {a[u].x, a[u].y, a[u].z, a[u].w};
                const uint32_t wb[4] = {b[u].x, b[u].y, b[u].z, b[u].w};
#pragma unroll
                for (int e = 0; e < 4; e++) {
                    const float gl = bflo(wa[e]), gh = bfhi(wa[e]), ul = bflo(wb[e]), uh = bfhi(wb[e]);
                    ag[0][2 * e] = fmaf(x0, gl, ag[0][2 * e]);
                    ag[0][2 * e + 1] = fmaf(x0, gh, ag[0][2 * e + 1]);
                    ag[1][2 * e] = fmaf(x1, gl, ag[1][2 * e]);
                    ag[1][2 * e + 1] = fmaf(x1, gh, ag[1][2 * e + 1]);
                    au[0][2 * e] = fmaf(x0, ul, au[0][2 * e]);
                    au[0][2 * e + 1] = fmaf(x0, uh, au[0][2 * e + 1]);
                    au[1][2 * e] = fmaf(x1, ul, au[1][2 * e]);
                    au[1][2 * e + 1] = fmaf(x1, uh, au[1][2 * e + 1]);
                }
            }
        }
#pragma unroll
        for (int e = 0; e < 8; e++) {
            red[(rg * 4 + 0) * kD + cc * 8 + e] = ag[0][e];
            red[(rg * 4 + 1) * kD + cc * 8 + e] = ag[1][e];
            red[(rg * 4 + 2) * kD + cc * 8 + e] = au[0][e];
            red[(rg * 4 + 3) * kD + cc * 8 + e] = au[1][e];
        }
    }
    cta_sync();
    for (int i = t; i < 2 * kD; i += NT) {
        const int b = i / kD, c = i % kD;
        float gs = 0.f, us = 0.f;
#pragma unroll
        for (int r = 0; r < 4; r++) {
            gs += red[(r * 4 + b) * kD + c];
            us += red[(r * 4 + 2 + b) * kD + c];
        }
        hs[i] = bfr(bfr(sigmoidf_(bfr(gs))) * bfr(us));
    }
    cta_sync();
    if (t < 224) {
        float acc[2][8];
#pragma unroll
        for (int e = 0; e < 8; e++) acc[0][e] = acc[1][e] = 0.f;
        const __nv_bfloat16* pd = wd + (size_t)(j * 448 + rg) * kD + cc * 8;
        constexpr int U2 = 16;
        for (int i0 = 0; i0 < 112; i0 += U2) {
            uint4 a[U2];
#pragma unroll
            for (int u = 0; u < U2; u++) a[u] = ldg_nc128(pd + (size_t)(i0 + u) * 4 * kD);
#pragma unroll
            for (int u = 0; u < U2; u++) {
                const int row = rg + (i0 + u) * 4;
                const float h0 = hs[row], h1 = hs[kD + row];
                const uint32_t wa[4] = {a[u].x, a[u].y, a[u].z, a[u].w};
#pragma unroll
                for (int e = 0; e < 4; e++) {
                    const float lo = bflo(wa[e]), hi = bfhi(wa[e]);
                    acc[0][2 * e] = fmaf(h0, lo, acc[0][2 * e]);
                    acc[0][2 * e + 1] = fmaf(h0, hi, acc[0][2 * e + 1]);
                    acc[1][2 * e] = fmaf(h1, lo, acc[1][2 * e]);
                    acc[1][2 * e + 1] = fmaf(h1, hi, acc[1][2 * e + 1]);
                }
            }
        }
#pragma unroll
        for (int e = 0; e < 8; e++) {
            red[(rg * 2 + 0) * kD + cc * 8 + e] = acc[0][e];
            red[(rg * 2 + 1) * kD + cc * 8 + e] = acc[1][e];
        }
    }
    cta_sync();
    for (int i = t; i < 2 * kD; i += NT) {
        const int b = i / kD, c = i % kD;
        float s = 0.f;
#pragma unroll
        for (int r = 0; r < 4; r++) s += red[(r * 2 + b) * kD + c];
        box_st32(&g_outbox[b * 64 + c / 7][64 + j][c % 7], box_enc(s));
    }
}

__global__ void __launch_bounds__(NT, 1)
fused_decode_kernel(const __nv_bfloat16* __restrict__ x, const __nv_bfloat16* __restrict__ kc,
                    const __nv_bfloat16* __restrict__ vc, const __nv_bfloat16* __restrict__ wq,
                    const __nv_bfloat16* __restrict__ wo, const __nv_bfloat16* __restrict__ wg,
                    const __nv_bfloat16* __restrict__ wu, const __nv_bfloat16* __restrict__ wd,
                    const __nv_bfloat16* __restrict__ gate_w, __nv_bfloat16* __restrict__ out) {
    extern __shared__ __align__(1024) unsigned char smem[];
    const int cta = blockIdx.x;
    if (cta >= N_ATT) {
        glu_cta(smem, cta - N_ATT, x, wg, wu, wd);
        return;
    }
    const int tid = threadIdx.x, warp = tid >> 5, lane = tid & 31;
    const int grp = cta >> 2;
    const int r = cta & 3;
    const int b = grp >> 4, h = grp & 15;
    const uint32_t sbase = smem_u32(smem);
    const uint32_t ring = sbase + SM_RING + warp * (STAGES * SB);
    const uint32_t bars = sbase + SM_BAR + warp * ((STAGES + 1) * 8);
    const uint32_t sc = sbase + SM_SC + warp * (KPW * 4);

    const int qrg = tid >> 3, qc = tid & 7;
    uint4 wv[14];
    uint32_t xv[7];
    {
        const __nv_bfloat16* p = wq + (size_t)(qrg * 14) * kHD + h * kDH + r * 64 + qc * 8;
#pragma unroll
        for (int i = 0; i < 14; i++) wv[i] = ldg_nc128(p + (size_t)i * kHD);
#pragma unroll
        for (int i = 0; i < 7; i++) xv[i] = ldg_nc32(x + b * kD + qrg * 14 + i * 2);
    }

    const int gw = r * NW + warp;
    const char* kp = reinterpret_cast<const char*>(kc) + ((size_t)grp * kSK + (size_t)gw * KPS) * (kDH * 2);
    const char* vp = reinterpret_cast<const char*>(vc) + ((size_t)grp * kSK + (size_t)gw * KPS) * (kDH * 2);
    constexpr size_t CH_STRIDE = (size_t)GW * SB;
    if (lane == 0) {
#pragma unroll
        for (int s = 0; s <= STAGES; s++) mbar_init(bars + s * 8, 1);
        asm volatile("fence.mbarrier_init.release.cluster;" ::: "memory");
        asm volatile("fence.proxy.async.shared::cta;" ::: "memory");
#pragma unroll
        for (int s = 0; s < STAGES; s++) {
            mbar_expect_tx(bars + s * 8, SB);
            bulk_g2s(ring + s * SB, kp + s * CH_STRIDE, SB, bars + s * 8);
        }
    }
    __syncwarp();

    float gate = 0.f;
    if (warp == 0) {
        float s = 0.f;
#pragma unroll
        for (int i = 0; i < 7; i++) {
            const uint32_t xa = ldg_nc32(x + b * kD + (lane + 32 * i) * 2);
            const uint32_t ga = ldg_nc32(gate_w + (lane + 32 * i) * 2);
            s += bfr(bflo(xa) * bflo(ga)) + bfr(bfhi(xa) * bfhi(ga));
        }
#pragma unroll
        for (int o = 16; o; o >>= 1) s += __shfl_xor_sync(0xffffffffu, s, o);
        gate = bfr(sigmoidf_(bfr(s)));
    }

    {
        float acc[8];
#pragma unroll
        for (int e = 0; e < 8; e++) acc[e] = 0.f;
#pragma unroll
        for (int i = 0; i < 14; i++) {
            const float xi = (i & 1) ? bfhi(xv[i >> 1]) : bflo(xv[i >> 1]);
            acc[0] = fmaf(xi, bflo(wv[i].x), acc[0]);
            acc[1] = fmaf(xi, bfhi(wv[i].x), acc[1]);
            acc[2] = fmaf(xi, bflo(wv[i].y), acc[2]);
            acc[3] = fmaf(xi, bfhi(wv[i].y), acc[3]);
            acc[4] = fmaf(xi, bflo(wv[i].z), acc[4]);
            acc[5] = fmaf(xi, bfhi(wv[i].z), acc[5]);
            acc[6] = fmaf(xi, bflo(wv[i].w), acc[6]);
            acc[7] = fmaf(xi, bfhi(wv[i].w), acc[7]);
        }
#pragma unroll
        for (int e = 0; e < 8; e++) {
            acc[e] += __shfl_xor_sync(0xffffffffu, acc[e], 8);
            acc[e] += __shfl_xor_sync(0xffffffffu, acc[e], 16);
        }
        if (lane < 8) {
            const uint32_t a = sbase + SM_QP + (warp * 64 + lane * 8) * 4;
            sts128f(a, acc[0], acc[1], acc[2], acc[3]);
            sts128f(a + 16, acc[4], acc[5], acc[6], acc[7]);
        }
        cta_sync();
        const int c = tid & 63, dst = tid >> 6;
        float s = 0.f;
#pragma unroll
        for (int w = 0; w < NW; w++) s += ldsf(sbase + SM_QP + (w * 64 + c) * 4);
        s = bfr(s);
        float qv;
        if (dst == r) {
            qv = s;
        } else {
            box_st32(&g_qbox[grp * 4 + dst][r][c], box_enc(s));
            qv = box_poll32(&g_qbox[cta][dst][c]);
        }
        stsf(sbase + SM_Q + tid * 4, qv);
        cta_sync();
    }
    const int g4 = lane >> 3, sub = lane & 7;
    float q[32];
#pragma unroll
    for (int c = 0; c < 4; c++) {
        const uint4 a = lds128(sbase + SM_Q + ((sub + 8 * c) * 8) * 4);
        const uint4 bb = lds128(sbase + SM_Q + ((sub + 8 * c) * 8 + 4) * 4);
        q[c * 8 + 0] = __uint_as_float(a.x);
        q[c * 8 + 1] = __uint_as_float(a.y);
        q[c * 8 + 2] = __uint_as_float(a.z);
        q[c * 8 + 3] = __uint_as_float(a.w);
        q[c * 8 + 4] = __uint_as_float(bb.x);
        q[c * 8 + 5] = __uint_as_float(bb.y);
        q[c * 8 + 6] = __uint_as_float(bb.z);
        q[c * 8 + 7] = __uint_as_float(bb.w);
    }

    int s = 0;
    uint32_t ph = 0;
    for (int it = 0; it < NCH; it++) {
        mbar_wait(bars + s * 8, ph);
        const uint32_t a = ring + s * SB + g4 * 512 + sub * 16;
#pragma unroll
        for (int kg = 0; kg < KPS / 4; kg++) {
            float acc0 = 0.f, acc1 = 0.f;
#pragma unroll
            for (int c = 0; c < 4; c++) {
                const uint4 v = lds128(a + kg * 2048 + c * 128);
                acc0 = fmaf(bflo(v.x), q[c * 8 + 0], acc0);
                acc1 = fmaf(bfhi(v.x), q[c * 8 + 1], acc1);
                acc0 = fmaf(bflo(v.y), q[c * 8 + 2], acc0);
                acc1 = fmaf(bfhi(v.y), q[c * 8 + 3], acc1);
                acc0 = fmaf(bflo(v.z), q[c * 8 + 4], acc0);
                acc1 = fmaf(bfhi(v.z), q[c * 8 + 5], acc1);
                acc0 = fmaf(bflo(v.w), q[c * 8 + 6], acc0);
                acc1 = fmaf(bfhi(v.w), q[c * 8 + 7], acc1);
            }
            float t = acc0 + acc1;
            t += __shfl_xor_sync(0xffffffffu, t, 1);
            t += __shfl_xor_sync(0xffffffffu, t, 2);
            t += __shfl_xor_sync(0xffffffffu, t, 4);
            if (sub == 0) stsf(sc + (it * KPS + kg * 4 + g4) * 4, bfr(t) * 0.0625f);
        }
        __syncwarp();
        if (lane == 0) {
            const int nx = it + STAGES;
            const char* src = (nx < NCH) ? kp + (size_t)nx * CH_STRIDE : vp + (size_t)(nx - NCH) * CH_STRIDE;
            mbar_expect_tx(bars + s * 8, SB);
            bulk_g2s(ring + s * SB, src, SB, bars + s * 8);
        }
        if (++s == STAGES) { s = 0; ph ^= 1; }
    }

    constexpr float LOG2E = 1.4426950408889634f;
    float m_w, l_w;
    {
        const uint4 a = lds128(sc + lane * 32);
        const uint4 bb = lds128(sc + lane * 32 + 16);
        float v[8] = {__uint_as_float(a.x),  __uint_as_float(a.y),  __uint_as_float(a.z),  __uint_as_float(a.w),
                      __uint_as_float(bb.x), __uint_as_float(bb.y), __uint_as_float(bb.z), __uint_as_float(bb.w)};
        float m = v[0];
#pragma unroll
        for (int i = 1; i < 8; i++) m = fmaxf(m, v[i]);
#pragma unroll
        for (int o = 16; o; o >>= 1) m = fmaxf(m, __shfl_xor_sync(0xffffffffu, m, o));
        float l = 0.f;
#pragma unroll
        for (int i = 0; i < 8; i++) {
            v[i] = exp2f((v[i] - m) * LOG2E);
            l += v[i];
        }
#pragma unroll
        for (int o = 16; o; o >>= 1) l += __shfl_xor_sync(0xffffffffu, l, o);
        sts128f(sc + lane * 32, v[0], v[1], v[2], v[3]);
        sts128f(sc + lane * 32 + 16, v[4], v[5], v[6], v[7]);
        m_w = m;
        l_w = l;
        if (lane < 4) box_st64(&g_mlbox[grp * 4 + lane][gw], box_enc(m), box_enc(l));
        __syncwarp();
    }

    float o[8];
#pragma unroll
    for (int i = 0; i < 8; i++) o[i] = 0.f;
    uint2 ml = make_uint2(0u, 0u);
    uint32_t glu_w = 0u;
    for (int it = 0; it < NCH; it++) {
        if (it == NCH - 2) {
            ml = box_ld64(&g_mlbox[cta][lane]);
            if (warp == 0) glu_w = box_ld32(&g_outbox[cta][64 + (lane & 3)][lane >> 2]);
        }
        mbar_wait(bars + s * 8, ph);
        const uint32_t a = ring + s * SB + lane * 16;
#pragma unroll
        for (int kg = 0; kg < KPS / 4; kg++) {
            const uint4 pp = lds128(sc + (it * KPS + kg * 4) * 4);
            const float p[4] = {__uint_as_float(pp.x), __uint_as_float(pp.y), __uint_as_float(pp.z), __uint_as_float(pp.w)};
#pragma unroll
            for (int k = 0; k < 4; k++) {
                const uint4 v = lds128(a + (kg * 4 + k) * 512);
                o[0] = fmaf(bflo(v.x), p[k], o[0]);
                o[1] = fmaf(bfhi(v.x), p[k], o[1]);
                o[2] = fmaf(bflo(v.y), p[k], o[2]);
                o[3] = fmaf(bfhi(v.y), p[k], o[3]);
                o[4] = fmaf(bflo(v.z), p[k], o[4]);
                o[5] = fmaf(bfhi(v.z), p[k], o[5]);
                o[6] = fmaf(bflo(v.w), p[k], o[6]);
                o[7] = fmaf(bfhi(v.w), p[k], o[7]);
            }
        }
        __syncwarp();
        if (lane == 0) {
            const int nx = it + STAGES;
            if (nx < NCH) {
                mbar_expect_tx(bars + s * 8, SB);
                bulk_g2s(ring + s * SB, vp + (size_t)nx * CH_STRIDE, SB, bars + s * 8);
            }
            if (nx == NCH - 1) {
                mbar_expect_tx(bars + STAGES * 8, WO_WARP_BYTES);
                bulk_g2s(sbase + SM_WO + warp * WO_WARP_BYTES, wo + (size_t)(h * kDH + r * 64 + warp * 8) * kD,
                         WO_WARP_BYTES, bars + STAGES * 8);
            }
        }
        if (++s == STAGES) { s = 0; ph ^= 1; }
    }

    {
        unsigned n = 0;
        while (ml.x == 0u || ml.y == 0u) {
            ml = box_ld64(&g_mlbox[cta][lane]);
            if (++n > SPIN_LIMIT) __trap();
        }
        const float mi = __uint_as_float(ml.x), li = __uint_as_float(ml.y);
        float M = mi;
#pragma unroll
        for (int of = 16; of; of >>= 1) M = fmaxf(M, __shfl_xor_sync(0xffffffffu, M, of));
        float L = li * exp2f((mi - M) * LOG2E);
#pragma unroll
        for (int of = 16; of; of >>= 1) L += __shfl_xor_sync(0xffffffffu, L, of);
        const float scale = exp2f((m_w - M) * LOG2E) / L;
        sts128f(ring + lane * 32, o[0] * scale, o[1] * scale, o[2] * scale, o[3] * scale);
        sts128f(ring + lane * 32 + 16, o[4] * scale, o[5] * scale, o[6] * scale, o[7] * scale);
    }
    (void)l_w;
    cta_sync();
    if (warp == 1) box_st64(&g_mlbox[cta][lane], 0u, 0u);
    {
        float v = 0.f;
#pragma unroll
        for (int w = 0; w < NW; w++) v += ldsf(sbase + SM_RING + w * (STAGES * SB) + tid * 4);
        box_st32(&g_obox[grp * 4 + (tid >> 6)][r][tid & 63], box_enc(v));
    }
    float of = box_poll32(&g_obox[cta][g4][warp * 8 + sub]);
    of += __shfl_xor_sync(0xffffffffu, of, 8);
    of += __shfl_xor_sync(0xffffffffu, of, 16);
    of = bfr(of);

    mbar_wait(bars + STAGES * 8, 0);
    {
        float acc[14];
#pragma unroll
        for (int j = 0; j < 14; j++) acc[j] = 0.f;
        const uint32_t wbase = sbase + SM_WO + warp * WO_WARP_BYTES + lane * 4;
#pragma unroll
        for (int i = 0; i < 8; i++) {
            const float oi = __shfl_sync(0xffffffffu, of, i);
#pragma unroll
            for (int j = 0; j < 7; j++) {
                const uint32_t u = lds32(wbase + i * (kD * 2) + j * 128);
                acc[2 * j] = fmaf(oi, bflo(u), acc[2 * j]);
                acc[2 * j + 1] = fmaf(oi, bfhi(u), acc[2 * j + 1]);
            }
        }
#pragma unroll
        for (int j = 0; j < 7; j++) sts64f(ring + SB + (lane + 32 * j) * 8, acc[2 * j], acc[2 * j + 1]);
    }
    cta_sync();
    {
        const int src = cta & 63;
#pragma unroll
        for (int k = 0; k < 2; k++) {
            const int c = tid + k * NT;
            if (c < kD) {
                float v = 0.f;
#pragma unroll
                for (int w = 0; w < NW; w++) v += ldsf(sbase + SM_RING + w * (STAGES * SB) + SB + c * 4);
                box_st32(&g_outbox[b * 64 + c / 7][src][c % 7], box_enc(v));
            }
        }
    }
    if (warp != 0) return;

    {
        float v[8];
        uint4 a0, a1, b0, b1;
        unsigned n = 0;
        unsigned int* p0 = &g_outbox[cta][lane][0];
        unsigned int* p1 = &g_outbox[cta][lane + 32][0];
        do {
            a0 = box_ld128(p0);
            a1 = box_ld128(p0 + 4);
            b0 = box_ld128(p1);
            b1 = box_ld128(p1 + 4);
            if (++n > SPIN_LIMIT) __trap();
        } while (a0.x == 0u || a0.y == 0u || a0.z == 0u || a0.w == 0u || a1.x == 0u || a1.y == 0u || a1.z == 0u ||
                 b0.x == 0u || b0.y == 0u || b0.z == 0u || b0.w == 0u || b1.x == 0u || b1.y == 0u || b1.z == 0u);
        v[0] = __uint_as_float(a0.x) + __uint_as_float(b0.x);
        v[1] = __uint_as_float(a0.y) + __uint_as_float(b0.y);
        v[2] = __uint_as_float(a0.z) + __uint_as_float(b0.z);
        v[3] = __uint_as_float(a0.w) + __uint_as_float(b0.w);
        v[4] = __uint_as_float(a1.x) + __uint_as_float(b1.x);
        v[5] = __uint_as_float(a1.y) + __uint_as_float(b1.y);
        v[6] = __uint_as_float(a1.z) + __uint_as_float(b1.z);
        v[7] = 0.f;
        const bool h16 = lane & 16, h8 = lane & 8, h4 = lane & 4;
        float w4[4], w2[2], w1;
#pragma unroll
        for (int i = 0; i < 4; i++) {
            const float keep = h16 ? v[4 + i] : v[i], send = h16 ? v[i] : v[4 + i];
            w4[i] = keep + __shfl_xor_sync(0xffffffffu, send, 16);
        }
#pragma unroll
        for (int i = 0; i < 2; i++) {
            const float keep = h8 ? w4[2 + i] : w4[i], send = h8 ? w4[i] : w4[2 + i];
            w2[i] = keep + __shfl_xor_sync(0xffffffffu, send, 8);
        }
        {
            const float keep = h4 ? w2[1] : w2[0], send = h4 ? w2[0] : w2[1];
            w1 = keep + __shfl_xor_sync(0xffffffffu, send, 4);
        }
        w1 += __shfl_xor_sync(0xffffffffu, w1, 2);
        w1 += __shfl_xor_sync(0xffffffffu, w1, 1);
        const int col = lane >> 2;
        unsigned int* pg = &g_outbox[cta][64 + (lane & 3)][col];
        n = 0;
        while (col < 7 && glu_w == 0u) {
            glu_w = box_ld32(pg);
            if (++n > SPIN_LIMIT) __trap();
        }
        float bsum = (col < 7) ? __uint_as_float(glu_w) : 0.f;
        bsum += __shfl_xor_sync(0xffffffffu, bsum, 1);
        bsum += __shfl_xor_sync(0xffffffffu, bsum, 2);
        if ((lane & 3) == 0 && col < 7) {
            const float av = bfr(w1), bv = bfr(bsum);
            const float res = bfr(gate * av) + bfr(bfr(1.0f - gate) * bv);
            out[b * kD + (cta & 63) * 7 + col] = __float2bfloat16_rn(res);
        }
        box_st128(p0, 0u, 0u, 0u, 0u);
        box_st128(p0 + 4, 0u, 0u, 0u, 0u);
        box_st128(p1, 0u, 0u, 0u, 0u);
        box_st128(p1 + 4, 0u, 0u, 0u, 0u);
        box_st32(pg, 0u);
    }
}

}

extern "C" void kernel_launch(void* const* d_in, const int* in_sizes, int n_in, void* d_out, int out_size) {
    (void)in_sizes;
    (void)n_in;
    (void)out_size;
    const __nv_bfloat16* x = (const __nv_bfloat16*)d_in[0];
    const __nv_bfloat16* kc = (const __nv_bfloat16*)d_in[1];
    const __nv_bfloat16* vc = (const __nv_bfloat16*)d_in[2];
    const __nv_bfloat16* wq = (const __nv_bfloat16*)d_in[3];
    const __nv_bfloat16* wo = (const __nv_bfloat16*)d_in[4];
    const __nv_bfloat16* wg = (const __nv_bfloat16*)d_in[6];
    const __nv_bfloat16* wu = (const __nv_bfloat16*)d_in[7];
    const __nv_bfloat16* wd = (const __nv_bfloat16*)d_in[8];
    const __nv_bfloat16* gw = (const __nv_bfloat16*)d_in[9];
    static bool configured = false;
    if (!configured) {
        cudaFuncSetAttribute(fused_decode_kernel, cudaFuncAttributeMaxDynamicSharedMemorySize, SM_TOTAL);
        configured = true;
    }
    fused_decode_kernel<<<N_ATT + N_GLU, NT, SM_TOTAL>>>(x, kc, vc, wq, wo, wg, wu, wd, gw, (__nv_bfloat16*)d_out);
}
```

```cpp
#include <cuda_runtime.h>
#include <cuda.h>
#include <cuda_bf16.h>
#include <stdint.h>

namespace {

constexpr int kD = 448;
constexpr int kH = 16;
constexpr int kSK = 8192;
constexpr int kDH = 256;
constexpr int kF = 1792;
constexpr int kHD = kH * kDH;

constexpr int NW = 8;
constexpr int NT = NW * 32;
#define P_STAGES 3
#define P_UW 2
#define P_D0 2000
#define P_D1 150
#define P_WIN 8
#define P_LEAD 16
#define P_PERIOD 300
#define P_EARLY 4
#define P_WO_AT 64
constexpr int STAGES = P_STAGES;
constexpr int KPS = 8;
constexpr int SB = KPS * kDH * 2;
constexpr int GW = 4 * NW;
constexpr int NCH = kSK / KPS / GW;
constexpr int KPW = NCH * KPS;
constexpr int N_ATT = 128;
constexpr int N_GLU = 4;
constexpr int N_RED = kD / 8;
constexpr int NT_LAUNCH = NT + 64;
constexpr int UW = P_UW;
constexpr int UPR = NW / UW;
constexpr int UB = UW * SB;
constexpr int NS = UPR * STAGES;
constexpr int NC = 2 * NCH * UPR;
constexpr int WIN = P_WIN / UW, LEAD = P_LEAD / UW, WO_AT = P_WO_AT / UW;
constexpr int WO_BYTES = 64 * kD * 2;
constexpr int WQ_BYTES = 224 * 128;

constexpr int SM_RING = 0;
constexpr int SM_WO = SM_RING + NW * STAGES * SB;
constexpr int SM_SC = SM_WO + WO_BYTES;
constexpr int SM_Q = SM_SC + NW * KPW * 4;
constexpr int SM_QP = SM_Q + kDH * 4;
constexpr int SM_X = SM_QP + NW * 128 * 4;
constexpr int SM_OB = SM_X + 224 * 8;
constexpr int SM_FLAG = SM_OB + 128;
constexpr int BAR_FULL = SM_FLAG + 16;
constexpr int BAR_EMPTY = BAR_FULL + NS * 8;
constexpr int BAR_WQ = BAR_EMPTY + NS * 8;
constexpr int BAR_WO = BAR_WQ + 8;
constexpr int SM_ATT_TOTAL = BAR_WO + 8;
static_assert(SM_ATT_TOTAL <= 232448 - 1024, "smem");

constexpr unsigned SPIN_LIMIT = 1u << 22;

__device__ __align__(128) unsigned int g_qbox[N_ATT / 4][2][kDH];
__device__ __align__(128) uint2 g_mlbox[N_ATT / 4][GW];
__device__ __align__(128) unsigned int g_obox[N_ATT][4][64];
__device__ __align__(128) unsigned int g_outbox[2 * N_RED][64 + N_GLU][8];
__device__ __align__(128) unsigned int g_progress;

#define TL(k)
#define TL_INIT()
#define TL_FLUSH()

__device__ __forceinline__ uint32_t smem_u32(const void* p) { return (uint32_t)__cvta_generic_to_shared(p); }
__device__ __forceinline__ bool elect_one() {
    uint32_t pred;
    asm volatile("{\n .reg .pred p;\n elect.sync _|p, 0xffffffff;\n selp.u32 %0, 1, 0, p;\n }" : "=r"(pred));
    return pred != 0;
}
__device__ __forceinline__ void mbar_init(uint32_t bar, uint32_t cnt) {
    asm volatile("mbarrier.init.shared::cta.b64 [%0], %1;" ::"r"(bar), "r"(cnt) : "memory");
}
__device__ __forceinline__ void mbar_expect_tx(uint32_t bar, uint32_t bytes) {
    asm volatile("mbarrier.arrive.expect_tx.shared::cta.b64 _, [%0], %1;" ::"r"(bar), "r"(bytes) : "memory");
}
__device__ __forceinline__ void mbar_arrive(uint32_t bar) {
    asm volatile("mbarrier.arrive.shared::cta.b64 _, [%0];" ::"r"(bar) : "memory");
}
__device__ __forceinline__ bool mbar_try_wait(uint32_t bar, uint32_t parity) {
    uint32_t ok;
    asm volatile(
        "{\n .reg .pred p;\n mbarrier.try_wait.parity.shared::cta.b64 p, [%1], %2;\n selp.u32 %0, 1, 0, p;\n }"
        : "=r"(ok)
        : "r"(bar), "r"(parity)
        : "memory");
    return ok != 0;
}
__device__ __forceinline__ bool mbar_test_wait(uint32_t bar, uint32_t parity) {
    uint32_t ok;
    asm volatile(
        "{\n .reg .pred p;\n mbarrier.test_wait.parity.shared::cta.b64 p, [%1], %2;\n selp.u32 %0, 1, 0, p;\n }"
        : "=r"(ok)
        : "r"(bar), "r"(parity)
        : "memory");
    return ok != 0;
}
__device__ __forceinline__ void mbar_wait(uint32_t bar, uint32_t parity) {
    unsigned n = 0;
    while (!__all_sync(0xffffffffu, mbar_try_wait(bar, parity))) {
        if (++n > SPIN_LIMIT) __trap();
    }
}
__device__ __forceinline__ void bulk_g2s(uint32_t dst, const void* src, uint32_t bytes, uint32_t bar) {
    asm volatile("cp.async.bulk.shared::cluster.global.mbarrier::complete_tx::bytes [%0], [%1], %2, [%3];" ::"r"(dst),
                 "l"(src), "r"(bytes), "r"(bar)
                 : "memory");
}
__device__ __forceinline__ void bulk_prefetch_l2(const void* src, uint32_t bytes) {
    asm volatile("cp.async.bulk.prefetch.L2.global [%0], %1;" ::"l"(src), "r"(bytes) : "memory");
}
__device__ __forceinline__ void tma_2d(uint32_t dst, const CUtensorMap* tm, int c0, int c1, uint32_t bar) {
    asm volatile("cp.async.bulk.tensor.2d.shared::cluster.global.mbarrier::complete_tx::bytes [%0], [%1, {%3, %4}], [%2];"
                 ::"r"(dst), "l"(reinterpret_cast<uint64_t>(tm)), "r"(bar), "r"(c0), "r"(c1)
                 : "memory");
}
__device__ __forceinline__ void sts32(uint32_t a, uint32_t v) { asm volatile("st.shared.u32 [%0], %1;" ::"r"(a), "r"(v) : "memory"); }
__device__ __forceinline__ float2 lds64f(uint32_t a) {
    float2 v;
    asm volatile("ld.shared.v2.f32 {%0,%1}, [%2];" : "=f"(v.x), "=f"(v.y) : "r"(a) : "memory");
    return v;
}
__device__ __forceinline__ uint32_t clock32() {
    uint32_t c;
    asm volatile("mov.u32 %0, %%clock;" : "=r"(c));
    return c;
}
__device__ __forceinline__ uint4 lds128(uint32_t a) {
    uint4 v;
    asm volatile("ld.shared.v4.u32 {%0,%1,%2,%3}, [%4];" : "=r"(v.x), "=r"(v.y), "=r"(v.z), "=r"(v.w) : "r"(a) : "memory");
    return v;
}
__device__ __forceinline__ uint32_t lds32(uint32_t a) {
    uint32_t v;
    asm volatile("ld.shared.u32 %0, [%1];" : "=r"(v) : "r"(a) : "memory");
    return v;
}
__device__ __forceinline__ uint32_t flag_ld(uint32_t a) {
    uint32_t v;
    asm volatile("ld.volatile.shared.u32 %0, [%1];" : "=r"(v) : "r"(a) : "memory");
    return v;
}
__device__ __forceinline__ void flag_st(uint32_t a, uint32_t v) { asm volatile("st.volatile.shared.u32 [%0], %1;" ::"r"(a), "r"(v) : "memory"); }
__device__ __forceinline__ float ldsf(uint32_t a) { return __uint_as_float(lds32(a)); }
__device__ __forceinline__ void stsf(uint32_t a, float v) { asm volatile("st.shared.f32 [%0], %1;" ::"r"(a), "f"(v) : "memory"); }
__device__ __forceinline__ void sts64f(uint32_t a, float x, float y) {
    asm volatile("st.shared.v2.f32 [%0], {%1,%2};" ::"r"(a), "f"(x), "f"(y) : "memory");
}
__device__ __forceinline__ void sts128f(uint32_t a, float x, float y, float z, float w) {
    asm volatile("st.shared.v4.f32 [%0], {%1,%2,%3,%4};" ::"r"(a), "f"(x), "f"(y), "f"(z), "f"(w) : "memory");
}
__device__ __forceinline__ uint4 ldg_nc128(const void* p) {
    uint4 v;
    asm volatile("ld.global.nc.L1::no_allocate.v4.u32 {%0,%1,%2,%3}, [%4];" : "=r"(v.x), "=r"(v.y), "=r"(v.z), "=r"(v.w) : "l"(p));
    return v;
}
__device__ __forceinline__ uint32_t ldg_nc32(const void* p) {
    uint32_t v;
    asm volatile("ld.global.nc.u32 %0, [%1];" : "=r"(v) : "l"(p));
    return v;
}
__device__ __forceinline__ void box_st32(void* p, uint32_t v) { asm volatile("st.relaxed.gpu.global.u32 [%0], %1;" ::"l"(p), "r"(v) : "memory"); }
__device__ __forceinline__ void box_st64(void* p, uint32_t x, uint32_t y) {
    asm volatile("st.relaxed.gpu.global.v2.u32 [%0], {%1,%2};" ::"l"(p), "r"(x), "r"(y) : "memory");
}
__device__ __forceinline__ void box_st128(void* p, uint32_t x, uint32_t y, uint32_t z, uint32_t w) {
    asm volatile("st.relaxed.gpu.global.v4.u32 [%0], {%1,%2,%3,%4};" ::"l"(p), "r"(x), "r"(y), "r"(z), "r"(w) : "memory");
}
__device__ __forceinline__ uint32_t box_ld32(const void* p) {
    uint32_t v;
    asm volatile("ld.relaxed.gpu.global.u32 %0, [%1];" : "=r"(v) : "l"(p) : "memory");
    return v;
}
__device__ __forceinline__ uint2 box_ld64(const void* p) {
    uint2 v;
    asm volatile("ld.relaxed.gpu.global.v2.u32 {%0,%1}, [%2];" : "=r"(v.x), "=r"(v.y) : "l"(p) : "memory");
    return v;
}
__device__ __forceinline__ uint4 box_ld128(const void* p) {
    uint4 v;
    asm volatile("ld.relaxed.gpu.global.v4.u32 {%0,%1,%2,%3}, [%4];" : "=r"(v.x), "=r"(v.y), "=r"(v.z), "=r"(v.w) : "l"(p) : "memory");
    return v;
}
__device__ __forceinline__ uint32_t box_enc(float f) {
    uint32_t u = __float_as_uint(f);
    return u == 0u ? 0x80000000u : u;
}
__device__ __forceinline__ float box_poll32(unsigned int* p, uint32_t v) {
    unsigned n = 0;
    while (__any_sync(0xffffffffu, v == 0u)) {
        if (v == 0u) v = box_ld32(p);
        if (++n > SPIN_LIMIT) __trap();
    }
    box_st32(p, 0u);
    return __uint_as_float(v);
}
template <class T>
__device__ __forceinline__ T* pin(T* p) {
    asm volatile("" : "+l"(p));
    return p;
}
__device__ __forceinline__ uint32_t pin(uint32_t v) {
    asm volatile("" : "+r"(v));
    return v;
}
__device__ __forceinline__ bool landed(uint32_t v) {
    uint32_t r;
    asm volatile("or.b32 %0, %1, 1;" : "=r"(r) : "r"(v));
    return r != 0u;
}
__device__ __forceinline__ float bflo(uint32_t u) { return __uint_as_float(u << 16); }
__device__ __forceinline__ float bfhi(uint32_t u) { return __uint_as_float(u & 0xffff0000u); }
__device__ __forceinline__ float bfr(float f) { return __bfloat162float(__float2bfloat16_rn(f)); }
__device__ __forceinline__ float sigmoidf_(float v) { return 1.0f / (1.0f + __expf(-v)); }
__device__ __forceinline__ void cta_sync() { asm volatile("bar.sync 1, 256;" ::: "memory"); }

constexpr int G_ST = 6;
constexpr int G_SB = 4 * kD * 2;
constexpr int G_N1 = 28, G_N2 = 14;
constexpr int GSM_RING = 0;
constexpr int GSM_RED = GSM_RING + NW * G_ST * G_SB;
constexpr int GSM_X = GSM_RED + NW * 2 * kD * 4;
constexpr int GSM_H = GSM_X + 2 * kD * 4;
constexpr int GSM_BAR = GSM_H + 2 * kD * 4;
constexpr int GSM_TOTAL = GSM_BAR + NW * G_ST * 8;
static_assert(GSM_TOTAL <= 232448, "smem");
constexpr int SM_TOTAL = SM_ATT_TOTAL > GSM_TOTAL ? SM_ATT_TOTAL : GSM_TOTAL;

__device__ __forceinline__ void glu_cta(unsigned char* smem, int j, const __nv_bfloat16* __restrict__ x,
                                        const __nv_bfloat16* __restrict__ wg, const __nv_bfloat16* __restrict__ wu,
                                        const __nv_bfloat16* __restrict__ wd) {
    const int t = threadIdx.x, warp = __shfl_sync(0xffffffffu, t >> 5, 0), lane = t & 31;
    const uint32_t sbase = smem_u32(smem);
    const uint32_t ring = sbase + GSM_RING + warp * (G_ST * G_SB);
    const uint32_t bars = sbase + GSM_BAR + warp * (G_ST * 8);
    float* xs = reinterpret_cast<float*>(smem + GSM_X);
    float* hs = reinterpret_cast<float*>(smem + GSM_H);
    float* red = reinterpret_cast<float*>(smem + GSM_RED);
    const __nv_bfloat16* pg = wg + (size_t)(warp * 56) * kF + j * kD;
    const __nv_bfloat16* pu = wu + (size_t)(warp * 56) * kF + j * kD;
    const __nv_bfloat16* pd = wd + (size_t)(j * kD + warp * 56) * kD;
    auto issue = [&](int it, int s) {
        const uint32_t dst = ring + s * G_SB, bar = bars + s * 8;
        mbar_expect_tx(bar, G_SB);
        if (it < G_N1) {
            bulk_g2s(dst, pg + (size_t)(2 * it) * kF, kD * 2, bar);
            bulk_g2s(dst + kD * 2, pg + (size_t)(2 * it + 1) * kF, kD * 2, bar);
            bulk_g2s(dst + kD * 4, pu + (size_t)(2 * it) * kF, kD * 2, bar);
            bulk_g2s(dst + kD * 6, pu + (size_t)(2 * it + 1) * kF, kD * 2, bar);
        } else {
            bulk_g2s(dst, pd + (size_t)(it - G_N1) * 4 * kD, G_SB, bar);
        }
    };
    if (elect_one()) {
#pragma unroll
        for (int s = 0; s < G_ST; s++) mbar_init(bars + s * 8, 1);
        asm volatile("fence.mbarrier_init.release.cluster;" ::: "memory");
#pragma unroll
        for (int s = 0; s < G_ST; s++) issue(s, s);
    }
    for (int i = t; i < 2 * kD; i += NT) xs[i] = __bfloat162float(x[i]);
    cta_sync();
    int s = 0;
    uint32_t ph = 0;
    float ag[2][14], au[2][14];
#pragma unroll
    for (int e = 0; e < 14; e++) ag[0][e] = ag[1][e] = au[0][e] = au[1][e] = 0.f;
    for (int it = 0; it < G_N1; it++) {
        mbar_wait(bars + s * 8, ph);
        const uint32_t a = ring + s * G_SB + lane * 4;
#pragma unroll
        for (int k = 0; k < 2; k++) {
            const int row = warp * 56 + 2 * it + k;
            const float x0 = xs[row], x1 = xs[kD + row];
#pragma unroll
            for (int c = 0; c < 7; c++) {
                const uint32_t gv = lds32(a + k * (kD * 2) + c * 128);
                const uint32_t uv = lds32(a + (2 + k) * (kD * 2) + c * 128);
                ag[0][2 * c] = fmaf(x0, bflo(gv), ag[0][2 * c]);
                ag[0][2 * c + 1] = fmaf(x0, bfhi(gv), ag[0][2 * c + 1]);
                ag[1][2 * c] = fmaf(x1, bflo(gv), ag[1][2 * c]);
                ag[1][2 * c + 1] = fmaf(x1, bfhi(gv), ag[1][2 * c + 1]);
                au[0][2 * c] = fmaf(x0, bflo(uv), au[0][2 * c]);
                au[0][2 * c + 1] = fmaf(x0, bfhi(uv), au[0][2 * c + 1]);
                au[1][2 * c] = fmaf(x1, bflo(uv), au[1][2 * c]);
                au[1][2 * c + 1] = fmaf(x1, bfhi(uv), au[1][2 * c + 1]);
            }
        }
        __syncwarp();
        if (elect_one()) issue(it + G_ST, s);
        if (++s == G_ST) { s = 0; ph ^= 1; }
    }
    float gsum[4], usum[4];
#pragma unroll
    for (int c = 0; c < 7; c++) {
        *reinterpret_cast<float2*>(&red[(warp * 2 + 0) * kD + (lane + 32 * c) * 2]) = make_float2(ag[0][2 * c], ag[0][2 * c + 1]);
        *reinterpret_cast<float2*>(&red[(warp * 2 + 1) * kD + (lane + 32 * c) * 2]) = make_float2(ag[1][2 * c], ag[1][2 * c + 1]);
    }
    cta_sync();
#pragma unroll
    for (int k = 0; k < 4; k++) {
        const int i = t + k * NT;
        gsum[k] = 0.f;
        if (i < 2 * kD)
            for (int w = 0; w < NW; w++) gsum[k] += red[w * 2 * kD + i];
    }
    cta_sync();
#pragma unroll
    for (int c = 0; c < 7; c++) {
        *reinterpret_cast<float2*>(&red[(warp * 2 + 0) * kD + (lane + 32 * c) * 2]) = make_float2(au[0][2 * c], au[0][2 * c + 1]);
        *reinterpret_cast<float2*>(&red[(warp * 2 + 1) * kD + (lane + 32 * c) * 2]) = make_float2(au[1][2 * c], au[1][2 * c + 1]);
    }
    cta_sync();
#pragma unroll
    for (int k = 0; k < 4; k++) {
        const int i = t + k * NT;
        usum[k] = 0.f;
        if (i < 2 * kD) {
            for (int w = 0; w < NW; w++) usum[k] += red[w * 2 * kD + i];
            hs[i] = bfr(bfr(sigmoidf_(bfr(gsum[k]))) * bfr(usum[k]));
        }
    }
    cta_sync();
    float acc[2][14];
#pragma unroll
    for (int e = 0; e < 14; e++) acc[0][e] = acc[1][e] = 0.f;
    for (int it = 0; it < G_N2; it++) {
        mbar_wait(bars + s * 8, ph);
        const uint32_t a = ring + s * G_SB + lane * 4;
#pragma unroll
        for (int k = 0; k < 4; k++) {
            const int row = warp * 56 + 4 * it + k;
            const float h0 = hs[row], h1 = hs[kD + row];
#pragma unroll
            for (int c = 0; c < 7; c++) {
                const uint32_t dv = lds32(a + k * (kD * 2) + c * 128);
                acc[0][2 * c] = fmaf(h0, bflo(dv), acc[0][2 * c]);
                acc[0][2 * c + 1] = fmaf(h0, bfhi(dv), acc[0][2 * c + 1]);
                acc[1][2 * c] = fmaf(h1, bflo(dv), acc[1][2 * c]);
                acc[1][2 * c + 1] = fmaf(h1, bfhi(dv), acc[1][2 * c + 1]);
            }
        }
        __syncwarp();
        if (G_N1 + it + G_ST < G_N1 + G_N2 && elect_one()) issue(G_N1 + it + G_ST, s);
        if (++s == G_ST) { s = 0; ph ^= 1; }
    }
#pragma unroll
    for (int c = 0; c < 7; c++) {
        *reinterpret_cast<float2*>(&red[(warp * 2 + 0) * kD + (lane + 32 * c) * 2]) = make_float2(acc[0][2 * c], acc[0][2 * c + 1]);
        *reinterpret_cast<float2*>(&red[(warp * 2 + 1) * kD + (lane + 32 * c) * 2]) = make_float2(acc[1][2 * c], acc[1][2 * c + 1]);
    }
    cta_sync();
#pragma unroll
    for (int k = 0; k < 4; k++) {
        const int i = t + k * NT;
        if (i < 2 * kD) {
            float v = 0.f;
            for (int w = 0; w < NW; w++) v += red[w * 2 * kD + i];
            box_st32(&g_outbox[i >> 3][64 + j][i & 7], box_enc(v));
        }
    }
}

__global__ void __launch_bounds__(NT_LAUNCH, 1)
fused_decode_kernel(const __grid_constant__ CUtensorMap tm_wq, const __nv_bfloat16* __restrict__ x,
                    const __nv_bfloat16* __restrict__ kc, const __nv_bfloat16* __restrict__ vc,
                    const __nv_bfloat16* __restrict__ wo, const __nv_bfloat16* __restrict__ wg,
                    const __nv_bfloat16* __restrict__ wu, const __nv_bfloat16* __restrict__ wd,
                    const __nv_bfloat16* __restrict__ gate_w, __nv_bfloat16* __restrict__ out) {
    extern __shared__ __align__(1024) unsigned char smem[];
    const int cta = blockIdx.x;
    TL_INIT();
    TL(0);
    const int warp = __shfl_sync(0xffffffffu, (int)(threadIdx.x >> 5), 0);
    if (cta >= N_ATT) {
        if (warp >= NW) return;
        glu_cta(smem, cta - N_ATT, x, wg, wu, wd);
        TL(7);
        TL_FLUSH();
        return;
    }
    const int tid = threadIdx.x, lane = tid & 31;
    const int grp = cta >> 2;
    const int r = cta & 3;
    const int b = grp >> 4, h = grp & 15;
    const uint32_t sbase = smem_u32(smem);
    constexpr size_t CH_STRIDE = (size_t)GW * SB;
    constexpr float LOG2E = 1.4426950408889634f;

    if (warp == NW) {
        const uint32_t t0 = clock32();
        if (elect_one()) {
            mbar_init(sbase + BAR_WQ, 1);
            asm volatile("fence.mbarrier_init.release.cluster;" ::: "memory");
            mbar_expect_tx(sbase + BAR_WQ, WQ_BYTES);
            tma_2d(sbase + SM_WO, &tm_wq, h * kDH + r * 64, b * 224, sbase + BAR_WQ);
#pragma unroll
            for (int i = 0; i < NS; i++) {
                mbar_init(sbase + BAR_FULL + i * 8, 1);
                mbar_init(sbase + BAR_EMPTY + i * 8, UW);
            }
            mbar_init(sbase + BAR_WO, 1);
            flag_st(sbase + SM_FLAG, 0u);
            flag_st(sbase + SM_FLAG + 4, 0u);
            flag_st(sbase + SM_FLAG + 8, LEAD);
            asm volatile("fence.mbarrier_init.release.cluster;" ::: "memory");
        }
        __syncwarp();
        asm volatile("bar.arrive 2, 320;" ::: "memory");
        if (elect_one()) {
            const size_t off0 = ((size_t)grp * kSK + (size_t)(r * NW) * KPS) * (kDH * 2);
            const char* kp0 = reinterpret_cast<const char*>(kc) + off0;
            const char* vp0 = reinterpret_cast<const char*>(vc) + off0;
            int slot = 0;
            uint32_t eph = 1;
#pragma unroll 1
            for (int i = 0; i < NC; i++) {
                unsigned n = 0;
                if (i < NS) {
                    if (i < WIN) {
                        while (clock32() - t0 < (uint32_t)(P_D0 + i * (UW * P_D1))) {}
                    } else {
                        while (!mbar_test_wait(sbase + BAR_FULL + (i - WIN) * 8, 0) && flag_ld(sbase + SM_FLAG) == 0u) {
                            if (++n > SPIN_LIMIT) __trap();
                        }
                    }
                } else {
                    while (!mbar_try_wait(sbase + BAR_EMPTY + slot * 8, eph)) {
                        if (++n > SPIN_LIMIT) __trap();
                    }
                }
                n = 0;
                while ((uint32_t)i >= flag_ld(sbase + SM_FLAG + 8) && ++n < 512) {}
                const int j = i & (NC / 2 - 1);
                const char* src = (i < NC / 2 ? kp0 : vp0) + (size_t)(j / UPR) * CH_STRIDE + (j % UPR) * UB;
                mbar_expect_tx(sbase + BAR_FULL + slot * 8, UB);
                bulk_g2s(sbase + SM_RING + slot * UB, src, UB, sbase + BAR_FULL + slot * 8);
                flag_st(sbase + SM_FLAG + 4, i + 1);
                if (i == WO_AT) {
                    asm volatile("fence.proxy.async.shared::cta;" ::: "memory");
                    mbar_expect_tx(sbase + BAR_WO, WO_BYTES);
                    bulk_g2s(sbase + SM_WO, wo + (size_t)(h * kDH + r * 64) * kD, WO_BYTES, sbase + BAR_WO);
                }
                if (++slot == NS) { slot = 0; eph ^= 1; }
            }
        }
        return;
    }
    if (warp == NW + 1) {
        asm volatile("bar.sync 2, 320;" ::: "memory");
        {
            uint32_t rep = 0;
#pragma unroll 1
            for (unsigned n = 0;; n++) {
                const uint32_t cur = flag_ld(sbase + SM_FLAG + 4);
                uint32_t tot = 0;
                if (lane == 0) {
                    tot = atomicAdd(&g_progress, cur - rep) + (cur - rep);
                    if (tot == N_ATT * NC) box_st32(&g_progress, 0u);
                    flag_st(sbase + SM_FLAG + 8, tot / N_ATT + LEAD);
                }
                rep = __shfl_sync(0xffffffffu, cur, 0);
                if (rep == NC) break;
                __nanosleep(P_PERIOD);
                if (n > SPIN_LIMIT) __trap();
            }
        }
        const int red = cta & 63;
        if (red >= N_RED) return;
        __nv_bfloat16* outp = pin(out + b * kD + red * 8 + (lane >> 2));
        unsigned int* box = pin(&g_outbox[b * N_RED + red][0][0]);
        unsigned int* p0 = box + lane * 8;
        unsigned int* p1 = box + (lane + 32) * 8;
        uint4 a0 = box_ld128(p0), a1 = box_ld128(p0 + 4), b0 = box_ld128(p1), b1 = box_ld128(p1 + 4);
        float gate;
        {
            float sg = 0.f;
#pragma unroll
            for (int i = 0; i < 7; i++) {
                const uint32_t gx = ldg_nc32(x + b * kD + (lane + 32 * i) * 2);
                const uint32_t gg = ldg_nc32(gate_w + (lane + 32 * i) * 2);
                sg += bfr(bflo(gx) * bflo(gg)) + bfr(bfhi(gx) * bfhi(gg));
            }
#pragma unroll
            for (int of = 16; of; of >>= 1) sg += __shfl_xor_sync(0xffffffffu, sg, of);
            gate = bfr(sigmoidf_(bfr(sg)));
        }
        float bsum = box_poll32(box + (64 + (lane & 3)) * 8 + (lane >> 2), 0u);
        bsum += __shfl_xor_sync(0xffffffffu, bsum, 1);
        bsum += __shfl_xor_sync(0xffffffffu, bsum, 2);
        const float bterm = bfr(bfr(1.0f - gate) * bfr(bsum));
        unsigned n = 0;
        for (;;) {
            const bool ea = a0.x == 0u || a0.y == 0u || a0.z == 0u || a0.w == 0u || a1.x == 0u || a1.y == 0u || a1.z == 0u || a1.w == 0u;
            const bool eb = b0.x == 0u || b0.y == 0u || b0.z == 0u || b0.w == 0u || b1.x == 0u || b1.y == 0u || b1.z == 0u || b1.w == 0u;
            if (!__any_sync(0xffffffffu, ea || eb)) break;
            if (ea) {
                a0 = box_ld128(p0);
                a1 = box_ld128(p0 + 4);
            }
            if (eb) {
                b0 = box_ld128(p1);
                b1 = box_ld128(p1 + 4);
            }
            if (++n > SPIN_LIMIT) __trap();
        }
        __syncwarp();
        float v[8];
        v[0] = __uint_as_float(a0.x) + __uint_as_float(b0.x);
        v[1] = __uint_as_float(a0.y) + __uint_as_float(b0.y);
        v[2] = __uint_as_float(a0.z) + __uint_as_float(b0.z);
        v[3] = __uint_as_float(a0.w) + __uint_as_float(b0.w);
        v[4] = __uint_as_float(a1.x) + __uint_as_float(b1.x);
        v[5] = __uint_as_float(a1.y) + __uint_as_float(b1.y);
        v[6] = __uint_as_float(a1.z) + __uint_as_float(b1.z);
        v[7] = __uint_as_float(a1.w) + __uint_as_float(b1.w);
        const bool h16 = lane & 16, h8 = lane & 8, h4 = lane & 4;
        float w4[4], w2[2], w1;
#pragma unroll
        for (int i = 0; i < 4; i++) w4[i] = (h16 ? v[4 + i] : v[i]) + __shfl_xor_sync(0xffffffffu, h16 ? v[i] : v[4 + i], 16);
#pragma unroll
        for (int i = 0; i < 2; i++) w2[i] = (h8 ? w4[2 + i] : w4[i]) + __shfl_xor_sync(0xffffffffu, h8 ? w4[i] : w4[2 + i], 8);
        w1 = (h4 ? w2[1] : w2[0]) + __shfl_xor_sync(0xffffffffu, h4 ? w2[0] : w2[1], 4);
        w1 += __shfl_xor_sync(0xffffffffu, w1, 2);
        w1 += __shfl_xor_sync(0xffffffffu, w1, 1);
        if ((lane & 3) == 0) *outp = __float2bfloat16_rn(bfr(gate * bfr(w1)) + bterm);
        box_st128(p0, 0u, 0u, 0u, 0u);
        box_st128(p0 + 4, 0u, 0u, 0u, 0u);
        box_st128(p1, 0u, 0u, 0u, 0u);
        box_st128(p1 + 4, 0u, 0u, 0u, 0u);
        return;
    }

    const uint32_t ring = sbase + SM_RING + warp * SB;
    const uint32_t fullb = sbase + BAR_FULL + (warp / UW) * 8;
    const uint32_t sc = sbase + SM_SC + warp * (KPW * 4);
    const int g4 = lane >> 3, sub = lane & 7;
    const int gw = r * NW + warp;

    {
        if (tid < 224) {
            const float x0 = __bfloat162float(x[b * 224 + tid]), x1 = __bfloat162float(x[kD + b * 224 + tid]);
            sts64f(sbase + SM_X + tid * 8, x0, x1);
        }
        uint32_t q0 = box_ld32(&g_qbox[grp][0][tid]), q1 = box_ld32(&g_qbox[grp][1][tid]);
        asm volatile("bar.sync 2, 320;" ::: "memory");
        TL(8);
        mbar_wait(sbase + BAR_WQ, 0);
        const int rg = tid >> 3;
        float acc[16];
#pragma unroll
        for (int e = 0; e < 16; e++) acc[e] = 0.f;
#pragma unroll
        for (int i = 0; i < 7; i++) {
            const uint4 wv = lds128(sbase + SM_WO + (rg * 7 + i) * 128 + sub * 16);
            const float2 xv = lds64f(sbase + SM_X + (rg * 7 + i) * 8);
            const uint32_t w4[4] = {wv.x, wv.y, wv.z, wv.w};
#pragma unroll
            for (int e = 0; e < 4; e++) {
                const float lo = bflo(w4[e]), hi = bfhi(w4[e]);
                acc[2 * e] = fmaf(xv.x, lo, acc[2 * e]);
                acc[2 * e + 1] = fmaf(xv.x, hi, acc[2 * e + 1]);
                acc[8 + 2 * e] = fmaf(xv.y, lo, acc[8 + 2 * e]);
                acc[8 + 2 * e + 1] = fmaf(xv.y, hi, acc[8 + 2 * e + 1]);
            }
        }
        const bool t8 = lane & 8, t16 = lane & 16;
        float r8[8], r4[4];
#pragma unroll
        for (int e = 0; e < 8; e++) r8[e] = (t8 ? acc[8 + e] : acc[e]) + __shfl_xor_sync(0xffffffffu, t8 ? acc[e] : acc[8 + e], 8);
#pragma unroll
        for (int e = 0; e < 4; e++) r4[e] = (t16 ? r8[4 + e] : r8[e]) + __shfl_xor_sync(0xffffffffu, t16 ? r8[e] : r8[4 + e], 16);
        sts128f(sbase + SM_QP + (warp * 128 + (t8 ? 64 : 0) + sub * 8 + (t16 ? 4 : 0)) * 4, r4[0], r4[1], r4[2], r4[3]);
        TL(9);
        cta_sync();
        TL(10);
        if (tid < 128) {
            float t[NW];
#pragma unroll
            for (int w = 0; w < NW; w++) t[w] = ldsf(sbase + SM_QP + (w * 128 + tid) * 4);
            const float sum = ((t[0] + t[1]) + (t[2] + t[3])) + ((t[4] + t[5]) + (t[6] + t[7]));
            box_st32(&g_qbox[(tid >> 6) * kH + h][b][r * 64 + (tid & 63)], box_enc(sum));
        }
        unsigned n = 0;
        while (__any_sync(0xffffffffu, q0 == 0u || q1 == 0u)) {
            if (q0 == 0u) q0 = box_ld32(&g_qbox[grp][0][tid]);
            if (q1 == 0u) q1 = box_ld32(&g_qbox[grp][1][tid]);
            if (++n > SPIN_LIMIT) __trap();
        }
        TL(11);
        stsf(sbase + SM_Q + tid * 4, bfr(__uint_as_float(q0) + __uint_as_float(q1)));
        cta_sync();
        if (tid == 0) flag_st(sbase + SM_FLAG, 1u);
    }
    int s = 0;
    uint32_t ph = 0;
    {
        float q[32];
#pragma unroll
        for (int c = 0; c < 4; c++) {
            const uint4 qa = lds128(sbase + SM_Q + ((sub + 8 * c) * 8) * 4);
            const uint4 qb = lds128(sbase + SM_Q + ((sub + 8 * c) * 8 + 4) * 4);
            q[c * 8 + 0] = __uint_as_float(qa.x);
            q[c * 8 + 1] = __uint_as_float(qa.y);
            q[c * 8 + 2] = __uint_as_float(qa.z);
            q[c * 8 + 3] = __uint_as_float(qa.w);
            q[c * 8 + 4] = __uint_as_float(qb.x);
            q[c * 8 + 5] = __uint_as_float(qb.y);
            q[c * 8 + 6] = __uint_as_float(qb.z);
            q[c * 8 + 7] = __uint_as_float(qb.w);
        }
        TL(1);

#pragma unroll 1
        for (int it = 0; it < NCH; it++) {
            mbar_wait(fullb + s * (UPR * 8), ph);
            const uint32_t a = ring + s * (NW * SB) + g4 * 512 + sub * 16;
            uint4 v[KPS / 4][4];
#pragma unroll
            for (int kg = 0; kg < KPS / 4; kg++)
#pragma unroll
                for (int c = 0; c < 4; c++) v[kg][c] = lds128(a + kg * 2048 + c * 128);
            __syncwarp();
            if (elect_one()) mbar_arrive(fullb + NS * 8 + s * (UPR * 8));
#pragma unroll
            for (int kg = 0; kg < KPS / 4; kg++) {
                float acc0 = 0.f, acc1 = 0.f;
#pragma unroll
                for (int c = 0; c < 4; c++) {
                    acc0 = fmaf(bflo(v[kg][c].x), q[c * 8 + 0], acc0);
                    acc1 = fmaf(bfhi(v[kg][c].x), q[c * 8 + 1], acc1);
                    acc0 = fmaf(bflo(v[kg][c].y), q[c * 8 + 2], acc0);
                    acc1 = fmaf(bfhi(v[kg][c].y), q[c * 8 + 3], acc1);
                    acc0 = fmaf(bflo(v[kg][c].z), q[c * 8 + 4], acc0);
                    acc1 = fmaf(bfhi(v[kg][c].z), q[c * 8 + 5], acc1);
                    acc0 = fmaf(bflo(v[kg][c].w), q[c * 8 + 6], acc0);
                    acc1 = fmaf(bfhi(v[kg][c].w), q[c * 8 + 7], acc1);
                }
                float t = acc0 + acc1;
                t += __shfl_xor_sync(0xffffffffu, t, 1);
                t += __shfl_xor_sync(0xffffffffu, t, 2);
                t += __shfl_xor_sync(0xffffffffu, t, 4);
                if (sub == 0) stsf(sc + (it * KPS + kg * 4 + g4) * 4, bfr(t) * 0.0625f);
            }
            if (++s == STAGES) { s = 0; ph ^= 1; }
        }
        TL(2);
        __syncwarp();
    }

    float m_w;
    {
        const uint4 sa = lds128(sc + lane * 32);
        const uint4 sb = lds128(sc + lane * 32 + 16);
        float v[8] = {__uint_as_float(sa.x), __uint_as_float(sa.y), __uint_as_float(sa.z), __uint_as_float(sa.w),
                      __uint_as_float(sb.x), __uint_as_float(sb.y), __uint_as_float(sb.z), __uint_as_float(sb.w)};
        float m = v[0];
#pragma unroll
        for (int i = 1; i < 8; i++) m = fmaxf(m, v[i]);
#pragma unroll
        for (int of = 16; of; of >>= 1) m = fmaxf(m, __shfl_xor_sync(0xffffffffu, m, of));
        float l = 0.f;
#pragma unroll
        for (int i = 0; i < 8; i++) {
            v[i] = exp2f((v[i] - m) * LOG2E);
            l += v[i];
        }
#pragma unroll
        for (int of = 16; of; of >>= 1) l += __shfl_xor_sync(0xffffffffu, l, of);
        sts128f(sc + lane * 32, v[0], v[1], v[2], v[3]);
        sts128f(sc + lane * 32 + 16, v[4], v[5], v[6], v[7]);
        m_w = m;
        if (lane == 0) box_st64(&g_mlbox[grp][gw], box_enc(m), box_enc(l));
        __syncwarp();
    }

    uint32_t af[4][4][4];
    if (warp < 7) {
        mbar_wait(sbase + BAR_WO, 0);
        const uint32_t wa = sbase + SM_WO + ((g4 >> 1) * 8 + sub) * (kD * 2) + (warp * 64 + (g4 & 1) * 8) * 2;
#pragma unroll
        for (int i = 0; i < 4; i++)
#pragma unroll
            for (int ks = 0; ks < 4; ks++)
                asm volatile("ldmatrix.sync.aligned.m8n8.x4.trans.shared.b16 {%0,%1,%2,%3}, [%4];"
                             : "=r"(af[i][ks][0]), "=r"(af[i][ks][1]), "=r"(af[i][ks][2]), "=r"(af[i][ks][3])
                             : "r"(wa + ks * 16 * (kD * 2) + i * 32)
                             : "memory");
    } else {
#pragma unroll
        for (int i = 0; i < 4; i++)
#pragma unroll
            for (int ks = 0; ks < 4; ks++) af[i][ks][0] = af[i][ks][1] = af[i][ks][2] = af[i][ks][3] = 0u;
    }

    float o[8];
#pragma unroll
    for (int i = 0; i < 8; i++) o[i] = 0.f;
    float scale = 0.f;
    uint4 oa = make_uint4(0u, 0u, 0u, 0u), ob = oa;
    uint2 ml = make_uint2(0u, 0u);
    unsigned int* po = pin(&g_obox[cta][g4][sub * 8]);
    unsigned int* osend = pin(&g_obox[grp * 4 + (tid >> 6)][r][tid & 63]);
    unsigned int* asend = pin(&g_outbox[b * N_RED + (warp < 7 ? warp : 0) * 8 + (lane & 3) * 2][cta & 63][lane >> 2]);
    uint2* pml = pin(&g_mlbox[grp][lane]);
    const uint32_t a_ost = pin(ring + lane * 32);
    const uint32_t a_old = pin(sbase + SM_RING + tid * 4);
    const uint32_t a_obs = pin(sbase + SM_OB + ((((lane >> 3) & 1) * 2 + (lane >> 4)) * 8 + sub) * 4);
    const uint32_t a_obl = pin(sbase + SM_OB + (lane & 3) * 32);
    const uint32_t lane_p = pin((uint32_t)lane);
#pragma unroll 1
    for (int it = 0; it < NCH; it++) {
        if (it == NCH - P_EARLY) {
            ml = box_ld64(pml);
            if (warp == 7) {
                oa = box_ld128(po);
                ob = box_ld128(po + 4);
            }
        }
        mbar_wait(fullb + s * (UPR * 8), ph);
        const uint32_t a = ring + s * (NW * SB) + lane * 16;
        uint4 pp[KPS / 4], v[KPS];
#pragma unroll
        for (int kg = 0; kg < KPS / 4; kg++) pp[kg] = lds128(sc + (it * KPS + kg * 4) * 4);
#pragma unroll
        for (int k = 0; k < KPS; k++) v[k] = lds128(a + k * 512);
        __syncwarp();
        if (elect_one()) mbar_arrive(fullb + NS * 8 + s * (UPR * 8));
#pragma unroll
        for (int k = 0; k < KPS; k++) {
            const uint4 p4 = pp[k >> 2];
            const float p = __uint_as_float((k & 3) == 0 ? p4.x : (k & 3) == 1 ? p4.y : (k & 3) == 2 ? p4.z : p4.w);
            o[0] = fmaf(bflo(v[k].x), p, o[0]);
            o[1] = fmaf(bfhi(v[k].x), p, o[1]);
            o[2] = fmaf(bflo(v[k].y), p, o[2]);
            o[3] = fmaf(bfhi(v[k].y), p, o[3]);
            o[4] = fmaf(bflo(v[k].z), p, o[4]);
            o[5] = fmaf(bfhi(v[k].z), p, o[5]);
            o[6] = fmaf(bflo(v[k].w), p, o[6]);
            o[7] = fmaf(bfhi(v[k].w), p, o[7]);
        }
        if (it == NCH - 2) {
            unsigned n = 0;
            while (__any_sync(0xffffffffu, ml.x == 0u || ml.y == 0u)) {
                if (ml.x == 0u || ml.y == 0u) ml = box_ld64(pml);
                if (++n > SPIN_LIMIT) __trap();
            }
            const float mi = __uint_as_float(ml.x), li = __uint_as_float(ml.y);
            float M = mi;
#pragma unroll
            for (int of = 16; of; of >>= 1) M = fmaxf(M, __shfl_xor_sync(0xffffffffu, M, of));
            float L = li * exp2f((mi - M) * LOG2E);
#pragma unroll
            for (int of = 16; of; of >>= 1) L += __shfl_xor_sync(0xffffffffu, L, of);
            scale = exp2f((m_w - M) * LOG2E) / L;
            if (r == 0) {
                box_st32(&g_qbox[grp][0][tid], 0u);
                box_st32(&g_qbox[grp][1][tid], 0u);
            }
        }
        if (++s == STAGES) { s = 0; ph ^= 1; }
    }
    TL(3);

    sts128f(a_ost, o[0] * scale, o[1] * scale, o[2] * scale, o[3] * scale);
    sts128f(a_ost + 16, o[4] * scale, o[5] * scale, o[6] * scale, o[7] * scale);
    cta_sync();
    {
        float v[NW];
#pragma unroll
        for (int w = 0; w < NW; w++) v[w] = ldsf(a_old + w * SB);
        const float t = ((v[0] + v[1]) + (v[2] + v[3])) + ((v[4] + v[5]) + (v[6] + v[7]));
        box_st32(osend, box_enc(t));
    }
    if (warp == 7) {
        unsigned n = 0;
        for (;;) {
            const bool e = oa.x == 0u || oa.y == 0u || oa.z == 0u || oa.w == 0u || ob.x == 0u || ob.y == 0u || ob.z == 0u || ob.w == 0u;
            if (!__any_sync(0xffffffffu, e)) break;
            if (e) {
                oa = box_ld128(po);
                ob = box_ld128(po + 4);
            }
            if (++n > SPIN_LIMIT) __trap();
        }
        const bool t8 = lane_p & 8, t16 = lane_p & 16;
        const float lo[4] = {__uint_as_float(oa.x), __uint_as_float(oa.y), __uint_as_float(oa.z), __uint_as_float(oa.w)};
        const float hi[4] = {__uint_as_float(ob.x), __uint_as_float(ob.y), __uint_as_float(ob.z), __uint_as_float(ob.w)};
        float r4[4], r2[2];
#pragma unroll
        for (int e = 0; e < 4; e++) r4[e] = (t8 ? hi[e] : lo[e]) + __shfl_xor_sync(0xffffffffu, t8 ? lo[e] : hi[e], 8);
#pragma unroll
        for (int e = 0; e < 2; e++) r2[e] = (t16 ? r4[2 + e] : r4[e]) + __shfl_xor_sync(0xffffffffu, t16 ? r4[e] : r4[2 + e], 16);
        const __nv_bfloat162 pk = __floats2bfloat162_rn(r2[0], r2[1]);
        sts32(a_obs, *reinterpret_cast<const uint32_t*>(&pk));
        asm volatile("bar.arrive 1, 256;" ::: "memory");
        box_st128(po, 0u, 0u, 0u, 0u);
        box_st128(po + 4, 0u, 0u, 0u, 0u);
        if (r == 0) box_st64(pml, 0u, 0u);
        return;
    }
    cta_sync();
    TL(4);

    {
        const uint4 bl = lds128(a_obl), bh = lds128(a_obl + 16);
        const uint32_t bf[8] = {bl.x, bl.y, bl.z, bl.w, bh.x, bh.y, bh.z, bh.w};
        float c[4][4];
#pragma unroll
        for (int i = 0; i < 4; i++) c[i][0] = c[i][1] = c[i][2] = c[i][3] = 0.f;
#pragma unroll
        for (int ks = 0; ks < 4; ks++)
#pragma unroll
            for (int i = 0; i < 4; i++)
                asm volatile("mma.sync.aligned.m16n8k16.row.col.f32.bf16.bf16.f32 {%0,%1,%2,%3}, {%4,%5,%6,%7}, {%8,%9}, {%0,%1,%2,%3};"
                             : "+f"(c[i][0]), "+f"(c[i][1]), "+f"(c[i][2]), "+f"(c[i][3])
                             : "r"(af[i][ks][0]), "r"(af[i][ks][1]), "r"(af[i][ks][2]), "r"(af[i][ks][3]),
                               "r"(bf[2 * ks]), "r"(bf[2 * ks + 1]));
        const uint32_t t = lane_p & 3;
        const float v0 = (t & 2) ? ((t & 1) ? c[3][0] : c[2][0]) : ((t & 1) ? c[1][0] : c[0][0]);
        const float v1 = (t & 2) ? ((t & 1) ? c[3][2] : c[2][2]) : ((t & 1) ? c[1][2] : c[0][2]);
        box_st32(asend, box_enc(v0));
        box_st32(asend + (64 + N_GLU) * 8, box_enc(v1));
    }
    TL(5);
    TL_FLUSH();
}

}

typedef CUresult (*PFN_tmapEncodeTiled)(CUtensorMap*, CUtensorMapDataType, cuuint32_t, void*, const cuuint64_t*,
                                        const cuuint64_t*, const cuuint32_t*, const cuuint32_t*, CUtensorMapInterleave,
                                        CUtensorMapSwizzle, CUtensorMapL2promotion, CUtensorMapFloatOOBfill);

extern "C" void kernel_launch(void* const* d_in, const int* in_sizes, int n_in, void* d_out, int out_size) {
    (void)in_sizes;
    (void)n_in;
    (void)out_size;
    const __nv_bfloat16* x = (const __nv_bfloat16*)d_in[0];
    const __nv_bfloat16* kc = (const __nv_bfloat16*)d_in[1];
    const __nv_bfloat16* vc = (const __nv_bfloat16*)d_in[2];
    const __nv_bfloat16* wo = (const __nv_bfloat16*)d_in[4];
    const __nv_bfloat16* wg = (const __nv_bfloat16*)d_in[6];
    const __nv_bfloat16* wu = (const __nv_bfloat16*)d_in[7];
    const __nv_bfloat16* wd = (const __nv_bfloat16*)d_in[8];
    const __nv_bfloat16* gw = (const __nv_bfloat16*)d_in[9];
    static PFN_tmapEncodeTiled encode = nullptr;
    if (!encode) {
        cudaFuncSetAttribute(fused_decode_kernel, cudaFuncAttributeMaxDynamicSharedMemorySize, SM_TOTAL);
        void* fn = nullptr;
        cudaDriverEntryPointQueryResult qr;
        cudaGetDriverEntryPoint("cuTensorMapEncodeTiled", &fn, cudaEnableDefault, &qr);
        encode = (PFN_tmapEncodeTiled)fn;
    }
    CUtensorMap tm_wq;
    const cuuint64_t gdim[2] = {(cuuint64_t)kHD, (cuuint64_t)kD};
    const cuuint64_t gstride[1] = {(cuuint64_t)kHD * 2};
    const cuuint32_t box[2] = {64, 224};
    const cuuint32_t estr[2] = {1, 1};
    encode(&tm_wq, CU_TENSOR_MAP_DATA_TYPE_BFLOAT16, 2, d_in[3], gdim, gstride, box, estr, CU_TENSOR_MAP_INTERLEAVE_NONE,
           CU_TENSOR_MAP_SWIZZLE_NONE, CU_TENSOR_MAP_L2_PROMOTION_NONE, CU_TENSOR_MAP_FLOAT_OOB_FILL_NONE);
#define P_GRID (N_ATT + N_GLU)
    __nv_bfloat16* outp = (__nv_bfloat16*)d_out;
    void* args[] = {&tm_wq, &x, &kc, &vc, &wo, &wg, &wu, &wd, &gw, &outp};
    cudaLaunchCooperativeKernel((const void*)fused_decode_kernel, dim3(P_GRID), dim3(NT_LAUNCH), args, SM_TOTAL,
                                cudaStreamPerThread);
}
```

```cpp
#include <cuda_runtime.h>
#include <cuda.h>
#include <cuda_bf16.h>
#include <stdint.h>

namespace {

constexpr int kD = 448;
constexpr int kH = 16;
constexpr int kSK = 8192;
constexpr int kDH = 256;
constexpr int kF = 1792;
constexpr int kHD = kH * kDH;

constexpr int NW = 8;
constexpr int NT = NW * 32;
constexpr int NT_LAUNCH = NT + 96;
constexpr int N_ATT = 128;
constexpr int N_GLU = 4;
constexpr int N_RED = kD / 8;

constexpr int KPS = 8;
constexpr int SB = KPS * kDH * 2;
constexpr int GW = 4 * NW;
constexpr int NCH = kSK / KPS / GW;
constexpr int KPW = NCH * KPS;
constexpr int STAGES = 3;
constexpr int UW = 2;
constexpr int UPR = NW / UW;
constexpr int UB = UW * SB;
constexpr int NS = UPR * STAGES;
constexpr int NC = 2 * NCH * UPR;

constexpr int WIN = 4;
constexpr int T_FIRST = 2000, T_STEP = 300;
constexpr int LEAD = 8;
constexpr int LEAD_END = 4, END_AT = 220;
constexpr int PERIOD_NS = 50;
constexpr int WO_AT = 32;
constexpr int WO2_BACK = 2;

constexpr int WO_BYTES = 64 * kD * 2;
constexpr int WQ_BYTES = 224 * 128;

constexpr int SM_RING = 0;
constexpr int SM_WO = SM_RING + NW * STAGES * SB;
constexpr int SM_SC = SM_WO + WO_BYTES;
constexpr int SM_Q = SM_SC + NW * KPW * 4;
constexpr int SM_QP = SM_Q + kDH * 4;
constexpr int SM_X = SM_QP + NW * 128 * 4;
constexpr int SM_OB = SM_X + 224 * 8;
constexpr int SM_FLAG = SM_OB + 128;
constexpr int BAR_FULL = SM_FLAG + 16;
constexpr int BAR_EMPTY = BAR_FULL + NS * 8;
constexpr int BAR_WQ = BAR_EMPTY + NS * 8;
constexpr int BAR_WO = BAR_WQ + 8;
constexpr int SM_ATT_TOTAL = BAR_WO + 16;
static_assert(SM_WO % 1024 == 0, "swizzled tiles");
static_assert(SM_ATT_TOTAL <= 232448 - 1024, "smem");

constexpr unsigned SPIN_LIMIT = 1u << 22;

__device__ __align__(128) unsigned int g_qbox[N_ATT / 4][2][kDH];
__device__ __align__(128) uint2 g_mlbox[N_ATT / 4][GW];
__device__ __align__(128) unsigned int g_obox[N_ATT][4][64];
__device__ __align__(128) unsigned int g_outbox[2 * N_RED][64 + N_GLU][8];
__device__ __align__(128) unsigned int g_progress;

__device__ __forceinline__ uint32_t smem_u32(const void* p) { return (uint32_t)__cvta_generic_to_shared(p); }
__device__ __forceinline__ bool elect_one() {
    uint32_t pred;
    asm volatile("{\n .reg .pred p;\n elect.sync _|p, 0xffffffff;\n selp.u32 %0, 1, 0, p;\n }" : "=r"(pred));
    return pred != 0;
}
__device__ __forceinline__ void mbar_init(uint32_t bar, uint32_t cnt) {
    asm volatile("mbarrier.init.shared::cta.b64 [%0], %1;" ::"r"(bar), "r"(cnt) : "memory");
}
__device__ __forceinline__ void mbar_expect_tx(uint32_t bar, uint32_t bytes) {
    asm volatile("mbarrier.arrive.expect_tx.shared::cta.b64 _, [%0], %1;" ::"r"(bar), "r"(bytes) : "memory");
}
__device__ __forceinline__ void mbar_arrive(uint32_t bar) {
    asm volatile("mbarrier.arrive.shared::cta.b64 _, [%0];" ::"r"(bar) : "memory");
}
__device__ __forceinline__ bool mbar_try_wait(uint32_t bar, uint32_t parity) {
    uint32_t ok;
    asm volatile(
        "{\n .reg .pred p;\n mbarrier.try_wait.parity.shared::cta.b64 p, [%1], %2;\n selp.u32 %0, 1, 0, p;\n }"
        : "=r"(ok)
        : "r"(bar), "r"(parity)
        : "memory");
    return ok != 0;
}
__device__ __forceinline__ bool mbar_test_wait(uint32_t bar, uint32_t parity) {
    uint32_t ok;
    asm volatile(
        "{\n .reg .pred p;\n mbarrier.test_wait.parity.shared::cta.b64 p, [%1], %2;\n selp.u32 %0, 1, 0, p;\n }"
        : "=r"(ok)
        : "r"(bar), "r"(parity)
        : "memory");
    return ok != 0;
}
__device__ __forceinline__ void mbar_wait(uint32_t bar, uint32_t parity) {
    unsigned n = 0;
    while (!__all_sync(0xffffffffu, mbar_try_wait(bar, parity))) {
        if (++n > SPIN_LIMIT) __trap();
    }
}
__device__ __forceinline__ void bulk_g2s(uint32_t dst, const void* src, uint32_t bytes, uint32_t bar, uint64_t pol) {
    asm volatile("cp.async.bulk.shared::cluster.global.mbarrier::complete_tx::bytes.L2::cache_hint [%0], [%1], %2, [%3], %4;"
                 ::"r"(dst), "l"(src), "r"(bytes), "r"(bar), "l"(pol)
                 : "memory");
}
__device__ __forceinline__ void tma_2d(uint32_t dst, const CUtensorMap* tm, int c0, int c1, uint32_t bar) {
    asm volatile("cp.async.bulk.tensor.2d.shared::cluster.global.mbarrier::complete_tx::bytes [%0], [%1, {%3, %4}], [%2];"
                 ::"r"(dst), "l"(reinterpret_cast<uint64_t>(tm)), "r"(bar), "r"(c0), "r"(c1)
                 : "memory");
}
__device__ __forceinline__ float2 lds64f(uint32_t a) {
    float2 v;
    asm volatile("ld.shared.v2.f32 {%0,%1}, [%2];" : "=f"(v.x), "=f"(v.y) : "r"(a) : "memory");
    return v;
}
__device__ __forceinline__ uint32_t clock32() {
    uint32_t c;
    asm volatile("mov.u32 %0, %%clock;" : "=r"(c));
    return c;
}
__device__ __forceinline__ uint4 lds128(uint32_t a) {
    uint4 v;
    asm volatile("ld.shared.v4.u32 {%0,%1,%2,%3}, [%4];" : "=r"(v.x), "=r"(v.y), "=r"(v.z), "=r"(v.w) : "r"(a) : "memory");
    return v;
}
__device__ __forceinline__ uint32_t lds32(uint32_t a) {
    uint32_t v;
    asm volatile("ld.shared.u32 %0, [%1];" : "=r"(v) : "r"(a) : "memory");
    return v;
}
__device__ __forceinline__ uint32_t flag_ld(uint32_t a) {
    uint32_t v;
    asm volatile("ld.volatile.shared.u32 %0, [%1];" : "=r"(v) : "r"(a) : "memory");
    return v;
}
__device__ __forceinline__ void flag_st(uint32_t a, uint32_t v) { asm volatile("st.volatile.shared.u32 [%0], %1;" ::"r"(a), "r"(v) : "memory"); }
__device__ __forceinline__ float ldsf(uint32_t a) { return __uint_as_float(lds32(a)); }
__device__ __forceinline__ void stsf(uint32_t a, float v) { asm volatile("st.shared.f32 [%0], %1;" ::"r"(a), "f"(v) : "memory"); }
__device__ __forceinline__ void sts64f(uint32_t a, float x, float y) {
    asm volatile("st.shared.v2.f32 [%0], {%1,%2};" ::"r"(a), "f"(x), "f"(y) : "memory");
}
__device__ __forceinline__ void sts128f(uint32_t a, float x, float y, float z, float w) {
    asm volatile("st.shared.v4.f32 [%0], {%1,%2,%3,%4};" ::"r"(a), "f"(x), "f"(y), "f"(z), "f"(w) : "memory");
}
__device__ __forceinline__ uint32_t ldg_nc32(const void* p) {
    uint32_t v;
    asm volatile("ld.global.nc.u32 %0, [%1];" : "=r"(v) : "l"(p));
    return v;
}
__device__ __forceinline__ void box_st32(void* p, uint32_t v) { asm volatile("st.relaxed.gpu.global.u32 [%0], %1;" ::"l"(p), "r"(v) : "memory"); }
__device__ __forceinline__ void box_st64(void* p, uint32_t x, uint32_t y) {
    asm volatile("st.relaxed.gpu.global.v2.u32 [%0], {%1,%2};" ::"l"(p), "r"(x), "r"(y) : "memory");
}
__device__ __forceinline__ void box_st128(void* p, uint32_t x, uint32_t y, uint32_t z, uint32_t w) {
    asm volatile("st.relaxed.gpu.global.v4.u32 [%0], {%1,%2,%3,%4};" ::"l"(p), "r"(x), "r"(y), "r"(z), "r"(w) : "memory");
}
__device__ __forceinline__ uint32_t box_ld32(const void* p) {
    uint32_t v;
    asm volatile("ld.relaxed.gpu.global.u32 %0, [%1];" : "=r"(v) : "l"(p) : "memory");
    return v;
}
__device__ __forceinline__ uint2 box_ld64(const void* p) {
    uint2 v;
    asm volatile("ld.relaxed.gpu.global.v2.u32 {%0,%1}, [%2];" : "=r"(v.x), "=r"(v.y) : "l"(p) : "memory");
    return v;
}
__device__ __forceinline__ uint4 box_ld128(const void* p) {
    uint4 v;
    asm volatile("ld.relaxed.gpu.global.v4.u32 {%0,%1,%2,%3}, [%4];" : "=r"(v.x), "=r"(v.y), "=r"(v.z), "=r"(v.w) : "l"(p) : "memory");
    return v;
}
__device__ __forceinline__ uint32_t box_enc(float f) {
    uint32_t u = __float_as_uint(f);
    return u == 0u ? 0x80000000u : u;
}
template <class T>
__device__ __forceinline__ T* pin(T* p) {
    asm volatile("" : "+l"(p));
    return p;
}
__device__ __forceinline__ uint32_t pin(uint32_t v) {
    asm volatile("" : "+r"(v));
    return v;
}
__device__ __forceinline__ float bflo(uint32_t u) { return __uint_as_float(u << 16); }
__device__ __forceinline__ float bfhi(uint32_t u) { return __uint_as_float(u & 0xffff0000u); }
__device__ __forceinline__ float bfr(float f) {
    uint32_t u;
    asm("cvt.rn.bf16x2.f32 %0, %1, %2;" : "=r"(u) : "f"(f), "f"(0.f));
    return __uint_as_float(u);
}
__device__ __forceinline__ float sigmoidf_(float v) { return 1.0f / (1.0f + __expf(-v)); }
__device__ __forceinline__ void cta_sync() { asm volatile("bar.sync 1, 256;" ::: "memory"); }

constexpr int G_ST = 6;
constexpr int G_SB = 4 * kD * 2;
constexpr int G_N1 = 28, G_N2 = 14;
constexpr int GSM_RING = 0;
constexpr int GSM_RED = GSM_RING + NW * G_ST * G_SB;
constexpr int GSM_X = GSM_RED + NW * 2 * kD * 4;
constexpr int GSM_H = GSM_X + 2 * kD * 4;
constexpr int GSM_BAR = GSM_H + 2 * kD * 4;
constexpr int GSM_TOTAL = GSM_BAR + NW * G_ST * 8;
static_assert(GSM_TOTAL <= 232448, "smem");
constexpr int SM_TOTAL = SM_ATT_TOTAL > GSM_TOTAL ? SM_ATT_TOTAL : GSM_TOTAL;

__device__ __forceinline__ void glu_cta(unsigned char* smem, int j, const __nv_bfloat16* __restrict__ x,
                                        const __nv_bfloat16* __restrict__ wg, const __nv_bfloat16* __restrict__ wu,
                                        const __nv_bfloat16* __restrict__ wd) {
    const int t = threadIdx.x, warp = __shfl_sync(0xffffffffu, t >> 5, 0), lane = t & 31;
    const uint32_t sbase = smem_u32(smem);
    const uint32_t ring = sbase + GSM_RING + warp * (G_ST * G_SB);
    const uint32_t bars = sbase + GSM_BAR + warp * (G_ST * 8);
    float* xs = reinterpret_cast<float*>(smem + GSM_X);
    float* hs = reinterpret_cast<float*>(smem + GSM_H);
    float* red = reinterpret_cast<float*>(smem + GSM_RED);
    const __nv_bfloat16* pg = wg + (size_t)(warp * 56) * kF + j * kD;
    const __nv_bfloat16* pu = wu + (size_t)(warp * 56) * kF + j * kD;
    const __nv_bfloat16* pd = wd + (size_t)(j * kD + warp * 56) * kD;
    uint64_t pol;
    asm volatile("createpolicy.fractional.L2::evict_first.b64 %0, 1.0;" : "=l"(pol));
    auto issue = [&](int it, int s) {
        const uint32_t dst = ring + s * G_SB, bar = bars + s * 8;
        mbar_expect_tx(bar, G_SB);
        if (it < G_N1) {
            bulk_g2s(dst, pg + (size_t)(2 * it) * kF, kD * 2, bar, pol);
            bulk_g2s(dst + kD * 2, pg + (size_t)(2 * it + 1) * kF, kD * 2, bar, pol);
            bulk_g2s(dst + kD * 4, pu + (size_t)(2 * it) * kF, kD * 2, bar, pol);
            bulk_g2s(dst + kD * 6, pu + (size_t)(2 * it + 1) * kF, kD * 2, bar, pol);
        } else {
            bulk_g2s(dst, pd + (size_t)(it - G_N1) * 4 * kD, G_SB, bar, pol);
        }
    };
    if (elect_one()) {
#pragma unroll
        for (int s = 0; s < G_ST; s++) mbar_init(bars + s * 8, 1);
        asm volatile("fence.mbarrier_init.release.cluster;" ::: "memory");
#pragma unroll
        for (int s = 0; s < G_ST; s++) issue(s, s);
    }
    for (int i = t; i < 2 * kD; i += NT) xs[i] = __bfloat162float(x[i]);
    cta_sync();
    int s = 0;
    uint32_t ph = 0;
    float ag[2][14], au[2][14];
#pragma unroll
    for (int e = 0; e < 14; e++) ag[0][e] = ag[1][e] = au[0][e] = au[1][e] = 0.f;
    for (int it = 0; it < G_N1; it++) {
        mbar_wait(bars + s * 8, ph);
        const uint32_t a = ring + s * G_SB + lane * 4;
#pragma unroll
        for (int k = 0; k < 2; k++) {
            const int row = warp * 56 + 2 * it + k;
            const float x0 = xs[row], x1 = xs[kD + row];
#pragma unroll
            for (int c = 0; c < 7; c++) {
                const uint32_t gv = lds32(a + k * (kD * 2) + c * 128);
                const uint32_t uv = lds32(a + (2 + k) * (kD * 2) + c * 128);
                ag[0][2 * c] = fmaf(x0, bflo(gv), ag[0][2 * c]);
                ag[0][2 * c + 1] = fmaf(x0, bfhi(gv), ag[0][2 * c + 1]);
                ag[1][2 * c] = fmaf(x1, bflo(gv), ag[1][2 * c]);
                ag[1][2 * c + 1] = fmaf(x1, bfhi(gv), ag[1][2 * c + 1]);
                au[0][2 * c] = fmaf(x0, bflo(uv), au[0][2 * c]);
                au[0][2 * c + 1] = fmaf(x0, bfhi(uv), au[0][2 * c + 1]);
                au[1][2 * c] = fmaf(x1, bflo(uv), au[1][2 * c]);
                au[1][2 * c + 1] = fmaf(x1, bfhi(uv), au[1][2 * c + 1]);
            }
        }
        __syncwarp();
        if (elect_one()) issue(it + G_ST, s);
        if (++s == G_ST) { s = 0; ph ^= 1; }
    }
    float gsum[4], usum[4];
#pragma unroll
    for (int c = 0; c < 7; c++) {
        *reinterpret_cast<float2*>(&red[(warp * 2 + 0) * kD + (lane + 32 * c) * 2]) = make_float2(ag[0][2 * c], ag[0][2 * c + 1]);
        *reinterpret_cast<float2*>(&red[(warp * 2 + 1) * kD + (lane + 32 * c) * 2]) = make_float2(ag[1][2 * c], ag[1][2 * c + 1]);
    }
    cta_sync();
#pragma unroll
    for (int k = 0; k < 4; k++) {
        const int i = t + k * NT;
        gsum[k] = 0.f;
        if (i < 2 * kD)
            for (int w = 0; w < NW; w++) gsum[k] += red[w * 2 * kD + i];
    }
    cta_sync();
#pragma unroll
    for (int c = 0; c < 7; c++) {
        *reinterpret_cast<float2*>(&red[(warp * 2 + 0) * kD + (lane + 32 * c) * 2]) = make_float2(au[0][2 * c], au[0][2 * c + 1]);
        *reinterpret_cast<float2*>(&red[(warp * 2 + 1) * kD + (lane + 32 * c) * 2]) = make_float2(au[1][2 * c], au[1][2 * c + 1]);
    }
    cta_sync();
#pragma unroll
    for (int k = 0; k < 4; k++) {
        const int i = t + k * NT;
        usum[k] = 0.f;
        if (i < 2 * kD) {
            for (int w = 0; w < NW; w++) usum[k] += red[w * 2 * kD + i];
            hs[i] = bfr(bfr(sigmoidf_(bfr(gsum[k]))) * bfr(usum[k]));
        }
    }
    cta_sync();
    float acc[2][14];
#pragma unroll
    for (int e = 0; e < 14; e++) acc[0][e] = acc[1][e] = 0.f;
    for (int it = 0; it < G_N2; it++) {
        mbar_wait(bars + s * 8, ph);
        const uint32_t a = ring + s * G_SB + lane * 4;
#pragma unroll
        for (int k = 0; k < 4; k++) {
            const int row = warp * 56 + 4 * it + k;
            const float h0 = hs[row], h1 = hs[kD + row];
#pragma unroll
            for (int c = 0; c < 7; c++) {
                const uint32_t dv = lds32(a + k * (kD * 2) + c * 128);
                acc[0][2 * c] = fmaf(h0, bflo(dv), acc[0][2 * c]);
                acc[0][2 * c + 1] = fmaf(h0, bfhi(dv), acc[0][2 * c + 1]);
                acc[1][2 * c] = fmaf(h1, bflo(dv), acc[1][2 * c]);
                acc[1][2 * c + 1] = fmaf(h1, bfhi(dv), acc[1][2 * c + 1]);
            }
        }
        __syncwarp();
        if (G_N1 + it + G_ST < G_N1 + G_N2 && elect_one()) issue(G_N1 + it + G_ST, s);
        if (++s == G_ST) { s = 0; ph ^= 1; }
    }
#pragma unroll
    for (int c = 0; c < 7; c++) {
        *reinterpret_cast<float2*>(&red[(warp * 2 + 0) * kD + (lane + 32 * c) * 2]) = make_float2(acc[0][2 * c], acc[0][2 * c + 1]);
        *reinterpret_cast<float2*>(&red[(warp * 2 + 1) * kD + (lane + 32 * c) * 2]) = make_float2(acc[1][2 * c], acc[1][2 * c + 1]);
    }
    cta_sync();
#pragma unroll
    for (int k = 0; k < 4; k++) {
        const int i = t + k * NT;
        if (i < 2 * kD) {
            float v = 0.f;
            for (int w = 0; w < NW; w++) v += red[w * 2 * kD + i];
            box_st32(&g_outbox[i >> 3][64 + j][i & 7], box_enc(v));
        }
    }
}

__global__ void __launch_bounds__(NT_LAUNCH, 1)
fused_decode_kernel(const __grid_constant__ CUtensorMap tm_wq, const __grid_constant__ CUtensorMap tm_wo,
                    const __nv_bfloat16* __restrict__ x, const __nv_bfloat16* __restrict__ kc,
                    const __nv_bfloat16* __restrict__ vc, const __nv_bfloat16* __restrict__ wg,
                    const __nv_bfloat16* __restrict__ wu, const __nv_bfloat16* __restrict__ wd,
                    const __nv_bfloat16* __restrict__ gate_w, __nv_bfloat16* __restrict__ out) {
    extern __shared__ __align__(1024) unsigned char smem[];
    const int cta = blockIdx.x;
    const int warp = __shfl_sync(0xffffffffu, (int)(threadIdx.x >> 5), 0);
    if (cta >= N_ATT) {
        if (warp >= NW) return;
        glu_cta(smem, cta - N_ATT, x, wg, wu, wd);
        return;
    }
    const int tid = threadIdx.x, lane = tid & 31;
    const int grp = cta >> 2;
    const int r = cta & 3;
    const int b = grp >> 4, h = grp & 15;
    const uint32_t sbase = smem_u32(smem);
    constexpr size_t CH_STRIDE = (size_t)GW * SB;
    constexpr float LOG2E = 1.4426950408889634f;

    if (warp == NW) {
        const uint32_t t0 = clock32();
        if (elect_one()) {
            mbar_init(sbase + BAR_WQ, 1);
            asm volatile("fence.mbarrier_init.release.cluster;" ::: "memory");
            mbar_expect_tx(sbase + BAR_WQ, WQ_BYTES);
            tma_2d(sbase + SM_WO, &tm_wq, h * kDH + r * 64, b * 224, sbase + BAR_WQ);
#pragma unroll
            for (int i = 0; i < NS; i++) {
                mbar_init(sbase + BAR_FULL + i * 8, 1);
                mbar_init(sbase + BAR_EMPTY + i * 8, UW);
            }
            mbar_init(sbase + BAR_WO, 1);
            mbar_init(sbase + BAR_WO + 8, 1);
            flag_st(sbase + SM_FLAG, 0u);
            flag_st(sbase + SM_FLAG + 4, 0u);
            flag_st(sbase + SM_FLAG + 8, LEAD);
            asm volatile("fence.mbarrier_init.release.cluster;" ::: "memory");
        }
        __syncwarp();
        asm volatile("bar.arrive 2, 320;" ::: "memory");
        if (elect_one()) {
            const size_t off0 = ((size_t)grp * kSK + (size_t)(r * NW) * KPS) * (kDH * 2);
            const char* kp0 = reinterpret_cast<const char*>(kc) + off0;
            const char* vp0 = reinterpret_cast<const char*>(vc) + off0;
            uint64_t pol;
            asm volatile("createpolicy.fractional.L2::evict_first.b64 %0, 1.0;" : "=l"(pol));
            int slot = 0;
            uint32_t eph = 1;
#pragma unroll 1
            for (int i = 0; i < NC; i++) {
                unsigned n = 0;
                if (i < NS) {
                    if (i < WIN) {
                        while (clock32() - t0 < (uint32_t)(T_FIRST + i * T_STEP)) {}
                    } else {
                        while (!mbar_test_wait(sbase + BAR_FULL + (i - WIN) * 8, 0) && flag_ld(sbase + SM_FLAG) == 0u) {
                            if (++n > SPIN_LIMIT) __trap();
                        }
                    }
                } else {
                    while (!mbar_try_wait(sbase + BAR_EMPTY + slot * 8, eph)) {
                        if (++n > SPIN_LIMIT) __trap();
                    }
                }
                n = 0;
                while ((uint32_t)i >= flag_ld(sbase + SM_FLAG + 8) && ++n < 512) {}
                const int j = i & (NC / 2 - 1);
                const char* src = (i < NC / 2 ? kp0 : vp0) + (size_t)(j / UPR) * CH_STRIDE + (j % UPR) * UB;
                mbar_expect_tx(sbase + BAR_FULL + slot * 8, UB);
                bulk_g2s(sbase + SM_RING + slot * UB, src, UB, sbase + BAR_FULL + slot * 8, pol);
                flag_st(sbase + SM_FLAG + 4, i + 1);
                if (i == WO_AT) {
                    asm volatile("fence.proxy.async.shared::cta;" ::: "memory");
                    mbar_expect_tx(sbase + BAR_WO, WO_BYTES / 2);
#pragma unroll
                    for (int w = 0; w < 7; w++)
                        tma_2d(sbase + SM_WO + w * 8192, &tm_wo, w * 64, h * kDH + r * 64, sbase + BAR_WO);
                }
                if (++slot == NS) { slot = 0; eph ^= 1; }
            }
            {
                constexpr int u = NC - WO2_BACK;
                unsigned n = 0;
                while (!mbar_try_wait(sbase + BAR_FULL + (u % NS) * 8, (u / NS) & 1)) {
                    if (++n > SPIN_LIMIT) __trap();
                }
            }
            mbar_expect_tx(sbase + BAR_WO + 8, WO_BYTES / 2);
#pragma unroll
            for (int w = 0; w < 7; w++)
                tma_2d(sbase + SM_WO + w * 8192 + 4096, &tm_wo, w * 64, h * kDH + r * 64 + 32, sbase + BAR_WO + 8);
        }
        return;
    }
    if (warp == NW + 1) {
        const int red = cta & 63;
        const bool reducer = red < N_RED;
        __nv_bfloat16* outp = pin(out + b * kD + red * 8 + (lane >> 2));
        unsigned int* box = pin(&g_outbox[b * N_RED + (reducer ? red : 0)][0][0]);
        unsigned int* p0 = box + lane * 8;
        unsigned int* p1 = box + (lane + 32) * 8;
        unsigned int* pg = box + (64 + (lane & 3)) * 8 + (lane >> 2);
        float gate;
        {
            float sg = 0.f;
#pragma unroll
            for (int i = 0; i < 7; i++) {
                const uint32_t gx = ldg_nc32(x + b * kD + (lane + 32 * i) * 2);
                const uint32_t gg = ldg_nc32(gate_w + (lane + 32 * i) * 2);
                sg += bfr(bflo(gx) * bflo(gg)) + bfr(bfhi(gx) * bfhi(gg));
            }
#pragma unroll
            for (int of = 16; of; of >>= 1) sg += __shfl_xor_sync(0xffffffffu, sg, of);
            gate = bfr(sigmoidf_(bfr(sg)));
        }
        asm volatile("bar.sync 2, 320;" ::: "memory");
        {
            uint32_t rep = 0;
#pragma unroll 1
            for (unsigned n = 0;; n++) {
                const uint32_t cur = flag_ld(sbase + SM_FLAG + 4);
                if (lane == 0) {
                    uint32_t tot;
                    if (cur == rep) {
                        tot = box_ld32(&g_progress);
                    } else {
                        tot = atomicAdd(&g_progress, cur - rep) + (cur - rep);
                        if (tot == N_ATT * NC) box_st32(&g_progress, 0u);
                    }
                    flag_st(sbase + SM_FLAG + 8, tot / N_ATT + (tot < END_AT * N_ATT ? LEAD : LEAD_END));
                }
                rep = __shfl_sync(0xffffffffu, cur, 0);
                if (rep == NC) break;
                __nanosleep(PERIOD_NS);
                if (n > SPIN_LIMIT) __trap();
            }
        }
        if (!reducer) return;
        uint4 a0 = make_uint4(0u, 0u, 0u, 0u), a1 = a0, b0 = a0, b1 = a0;
        uint32_t gl = 0u;
        float bterm = 0.f;
        bool have_b = false;
        for (unsigned n = 0;; n++) {
            const bool ea = a0.x == 0u || a0.y == 0u || a0.z == 0u || a0.w == 0u || a1.x == 0u || a1.y == 0u || a1.z == 0u || a1.w == 0u;
            const bool eb = b0.x == 0u || b0.y == 0u || b0.z == 0u || b0.w == 0u || b1.x == 0u || b1.y == 0u || b1.z == 0u || b1.w == 0u;
            if (have_b && !__any_sync(0xffffffffu, ea || eb)) break;
            if (ea) {
                a0 = box_ld128(p0);
                a1 = box_ld128(p0 + 4);
            }
            if (eb) {
                b0 = box_ld128(p1);
                b1 = box_ld128(p1 + 4);
            }
            if (!have_b) {
                if (gl == 0u) gl = box_ld32(pg);
                if (!__any_sync(0xffffffffu, gl == 0u)) {
                    have_b = true;
                    float bsum = __uint_as_float(gl);
                    bsum += __shfl_xor_sync(0xffffffffu, bsum, 1);
                    bsum += __shfl_xor_sync(0xffffffffu, bsum, 2);
                    bterm = bfr(bfr(1.0f - gate) * bfr(bsum));
                }
            }
            if (n > SPIN_LIMIT) __trap();
        }
        float v[8];
        v[0] = __uint_as_float(a0.x) + __uint_as_float(b0.x);
        v[1] = __uint_as_float(a0.y) + __uint_as_float(b0.y);
        v[2] = __uint_as_float(a0.z) + __uint_as_float(b0.z);
        v[3] = __uint_as_float(a0.w) + __uint_as_float(b0.w);
        v[4] = __uint_as_float(a1.x) + __uint_as_float(b1.x);
        v[5] = __uint_as_float(a1.y) + __uint_as_float(b1.y);
        v[6] = __uint_as_float(a1.z) + __uint_as_float(b1.z);
        v[7] = __uint_as_float(a1.w) + __uint_as_float(b1.w);
        const bool h16 = lane & 16, h8 = lane & 8, h4 = lane & 4;
        float w4[4], w2[2], w1;
#pragma unroll
        for (int i = 0; i < 4; i++) w4[i] = (h16 ? v[4 + i] : v[i]) + __shfl_xor_sync(0xffffffffu, h16 ? v[i] : v[4 + i], 16);
#pragma unroll
        for (int i = 0; i < 2; i++) w2[i] = (h8 ? w4[2 + i] : w4[i]) + __shfl_xor_sync(0xffffffffu, h8 ? w4[i] : w4[2 + i], 8);
        w1 = (h4 ? w2[1] : w2[0]) + __shfl_xor_sync(0xffffffffu, h4 ? w2[0] : w2[1], 4);
        w1 += __shfl_xor_sync(0xffffffffu, w1, 2);
        w1 += __shfl_xor_sync(0xffffffffu, w1, 1);
        if ((lane & 3) == 0) *outp = __float2bfloat16_rn(bfr(gate * bfr(w1)) + bterm);
        box_st128(p0, 0u, 0u, 0u, 0u);
        box_st128(p0 + 4, 0u, 0u, 0u, 0u);
        box_st128(p1, 0u, 0u, 0u, 0u);
        box_st128(p1 + 4, 0u, 0u, 0u, 0u);
        box_st32(pg, 0u);
        return;
    }

    if (warp == NW + 2) {
        {
            const unsigned int* pq = &g_qbox[grp][0][lane * 8];
            uint4 u[4];
#pragma unroll
            for (int k = 0; k < 4; k++) u[k] = make_uint4(0u, 0u, 0u, 0u);
            for (unsigned n = 0;; n++) {
                bool any = false;
#pragma unroll
                for (int k = 0; k < 4; k++) {
                    const bool e = u[k].x == 0u || u[k].y == 0u || u[k].z == 0u || u[k].w == 0u;
                    if (e) u[k] = box_ld128(pq + (k >> 1) * kDH + (k & 1) * 4);
                    any |= e;
                }
                if (!__any_sync(0xffffffffu, any)) break;
                if (n > SPIN_LIMIT) __trap();
            }
#pragma unroll
            for (int k = 0; k < 2; k++)
                sts128f(sbase + SM_Q + lane * 32 + k * 16, bfr(__uint_as_float(u[k].x) + __uint_as_float(u[2 + k].x)),
                        bfr(__uint_as_float(u[k].y) + __uint_as_float(u[2 + k].y)),
                        bfr(__uint_as_float(u[k].z) + __uint_as_float(u[2 + k].z)),
                        bfr(__uint_as_float(u[k].w) + __uint_as_float(u[2 + k].w)));
            asm volatile("bar.sync 4, 288;" ::: "memory");
            if (lane == 0) flag_st(sbase + SM_FLAG, 1u);
        }
        unsigned int* po = pin(&g_obox[cta][0][lane * 2]);
        for (unsigned n = 0; __any_sync(0xffffffffu, flag_ld(sbase + SM_FLAG + 4) < NC); n++) {
            __nanosleep(200);
            if (n > SPIN_LIMIT) __trap();
        }
        uint2 og[4];
#pragma unroll
        for (int k = 0; k < 4; k++) og[k] = make_uint2(0u, 0u);
        for (unsigned n = 0;; n++) {
            bool any = false;
#pragma unroll
            for (int k = 0; k < 4; k++) {
                const bool e = og[k].x == 0u || og[k].y == 0u;
                if (e) og[k] = box_ld64(po + k * 64);
                any |= e;
            }
            if (!__any_sync(0xffffffffu, any)) break;
            if (n > SPIN_LIMIT) __trap();
        }
        const float ox = (__uint_as_float(og[0].x) + __uint_as_float(og[1].x)) + (__uint_as_float(og[2].x) + __uint_as_float(og[3].x));
        const float oy = (__uint_as_float(og[0].y) + __uint_as_float(og[1].y)) + (__uint_as_float(og[2].y) + __uint_as_float(og[3].y));
        const __nv_bfloat162 pk = __floats2bfloat162_rn(ox, oy);
        flag_st(sbase + SM_OB + ((lane & 3) * 8 + (lane >> 2)) * 4, *reinterpret_cast<const uint32_t*>(&pk));
        asm volatile("bar.arrive 3, 256;" ::: "memory");
#pragma unroll
        for (int k = 0; k < 4; k++) box_st64(po + k * 64, 0u, 0u);
        if (r == 0) box_st64(&g_mlbox[grp][lane], 0u, 0u);
        return;
    }

    const uint32_t ring = sbase + SM_RING + warp * SB;
    const uint32_t fullb = sbase + BAR_FULL + (warp / UW) * 8;
    const uint32_t sc = sbase + SM_SC + warp * (KPW * 4);
    const int g4 = lane >> 3, sub = lane & 7;
    const int gw = r * NW + warp;

    {
        if (tid < 224) {
            const float x0 = __bfloat162float(x[b * 224 + tid]), x1 = __bfloat162float(x[kD + b * 224 + tid]);
            sts64f(sbase + SM_X + tid * 8, x0, x1);
        }
        asm volatile("bar.sync 2, 320;" ::: "memory");
        mbar_wait(sbase + BAR_WQ, 0);
        const int rg = tid >> 3;
        float acc[16];
#pragma unroll
        for (int e = 0; e < 16; e++) acc[e] = 0.f;
#pragma unroll
        for (int i = 0; i < 7; i++) {
            const uint4 wv = lds128(sbase + SM_WO + (rg * 7 + i) * 128 + sub * 16);
            const float2 xv = lds64f(sbase + SM_X + (rg * 7 + i) * 8);
            const uint32_t w4[4] = {wv.x, wv.y, wv.z, wv.w};
#pragma unroll
            for (int e = 0; e < 4; e++) {
                const float lo = bflo(w4[e]), hi = bfhi(w4[e]);
                acc[2 * e] = fmaf(xv.x, lo, acc[2 * e]);
                acc[2 * e + 1] = fmaf(xv.x, hi, acc[2 * e + 1]);
                acc[8 + 2 * e] = fmaf(xv.y, lo, acc[8 + 2 * e]);
                acc[8 + 2 * e + 1] = fmaf(xv.y, hi, acc[8 + 2 * e + 1]);
            }
        }
        const bool t8 = lane & 8, t16 = lane & 16;
        float r8[8], r4[4];
#pragma unroll
        for (int e = 0; e < 8; e++) r8[e] = (t8 ? acc[8 + e] : acc[e]) + __shfl_xor_sync(0xffffffffu, t8 ? acc[e] : acc[8 + e], 8);
#pragma unroll
        for (int e = 0; e < 4; e++) r4[e] = (t16 ? r8[4 + e] : r8[e]) + __shfl_xor_sync(0xffffffffu, t16 ? r8[e] : r8[4 + e], 16);
        sts128f(sbase + SM_QP + (warp * 128 + (t8 ? 64 : 0) + sub * 8 + (t16 ? 4 : 0)) * 4, r4[0], r4[1], r4[2], r4[3]);
        cta_sync();
        if (tid < 128) {
            float t[NW];
#pragma unroll
            for (int w = 0; w < NW; w++) t[w] = ldsf(sbase + SM_QP + (w * 128 + tid) * 4);
            const float sum = ((t[0] + t[1]) + (t[2] + t[3])) + ((t[4] + t[5]) + (t[6] + t[7]));
            box_st32(&g_qbox[(tid >> 6) * kH + h][b][r * 64 + (tid & 63)], box_enc(sum));
        }
        asm volatile("bar.sync 4, 288;" ::: "memory");
    }
    int s = 0;
    uint32_t ph = 0;
    {
        float q[32];
#pragma unroll
        for (int c = 0; c < 4; c++) {
            const uint4 qa = lds128(sbase + SM_Q + ((sub + 8 * c) * 8) * 4);
            const uint4 qb = lds128(sbase + SM_Q + ((sub + 8 * c) * 8 + 4) * 4);
            q[c * 8 + 0] = __uint_as_float(qa.x);
            q[c * 8 + 1] = __uint_as_float(qa.y);
            q[c * 8 + 2] = __uint_as_float(qa.z);
            q[c * 8 + 3] = __uint_as_float(qa.w);
            q[c * 8 + 4] = __uint_as_float(qb.x);
            q[c * 8 + 5] = __uint_as_float(qb.y);
            q[c * 8 + 6] = __uint_as_float(qb.z);
            q[c * 8 + 7] = __uint_as_float(qb.w);
        }

#pragma unroll 1
        for (int it = 0; it < NCH; it++) {
            mbar_wait(fullb + s * (UPR * 8), ph);
            const uint32_t a = ring + s * (NW * SB) + g4 * 512 + sub * 16;
            uint4 v[KPS / 4][4];
#pragma unroll
            for (int kg = 0; kg < KPS / 4; kg++)
#pragma unroll
                for (int c = 0; c < 4; c++) v[kg][c] = lds128(a + kg * 2048 + c * 128);
            __syncwarp();
            if (elect_one()) mbar_arrive(fullb + NS * 8 + s * (UPR * 8));
#pragma unroll
            for (int kg = 0; kg < KPS / 4; kg++) {
                float acc0 = 0.f, acc1 = 0.f;
#pragma unroll
                for (int c = 0; c < 4; c++) {
                    acc0 = fmaf(bflo(v[kg][c].x), q[c * 8 + 0], acc0);
                    acc1 = fmaf(bfhi(v[kg][c].x), q[c * 8 + 1], acc1);
                    acc0 = fmaf(bflo(v[kg][c].y), q[c * 8 + 2], acc0);
                    acc1 = fmaf(bfhi(v[kg][c].y), q[c * 8 + 3], acc1);
                    acc0 = fmaf(bflo(v[kg][c].z), q[c * 8 + 4], acc0);
                    acc1 = fmaf(bfhi(v[kg][c].z), q[c * 8 + 5], acc1);
                    acc0 = fmaf(bflo(v[kg][c].w), q[c * 8 + 6], acc0);
                    acc1 = fmaf(bfhi(v[kg][c].w), q[c * 8 + 7], acc1);
                }
                float t = acc0 + acc1;
                t += __shfl_xor_sync(0xffffffffu, t, 1);
                t += __shfl_xor_sync(0xffffffffu, t, 2);
                t += __shfl_xor_sync(0xffffffffu, t, 4);
                if (sub == 0) stsf(sc + (it * KPS + kg * 4 + g4) * 4, bfr(t) * 0.0625f);
            }
            if (++s == STAGES) { s = 0; ph ^= 1; }
        }
        __syncwarp();
    }

    float m_w;
    {
        const uint4 sa = lds128(sc + lane * 32);
        const uint4 sb = lds128(sc + lane * 32 + 16);
        float v[8] = {__uint_as_float(sa.x), __uint_as_float(sa.y), __uint_as_float(sa.z), __uint_as_float(sa.w),
                      __uint_as_float(sb.x), __uint_as_float(sb.y), __uint_as_float(sb.z), __uint_as_float(sb.w)};
        float m = v[0];
#pragma unroll
        for (int i = 1; i < 8; i++) m = fmaxf(m, v[i]);
#pragma unroll
        for (int of = 16; of; of >>= 1) m = fmaxf(m, __shfl_xor_sync(0xffffffffu, m, of));
        float l = 0.f;
#pragma unroll
        for (int i = 0; i < 8; i++) {
            v[i] = exp2f((v[i] - m) * LOG2E);
            l += v[i];
        }
#pragma unroll
        for (int of = 16; of; of >>= 1) l += __shfl_xor_sync(0xffffffffu, l, of);
        sts128f(sc + lane * 32, v[0], v[1], v[2], v[3]);
        sts128f(sc + lane * 32 + 16, v[4], v[5], v[6], v[7]);
        m_w = m;
        if (lane == 0) box_st64(&g_mlbox[grp][gw], box_enc(m), box_enc(l));
        __syncwarp();
    }

    uint32_t af[4][4][4];
    const uint32_t a_wo = pin(sbase + SM_WO + (warp < 7 ? warp : 0) * 8192 + ((g4 >> 1) * 8 + sub) * 128);
    const uint32_t x_wo = pin((uint32_t)(((g4 & 1) ^ sub) << 4));
    auto load_wo = [&](int part) {
        mbar_wait(sbase + BAR_WO + part * 8, 0);
#pragma unroll
        for (int ks = 0; ks < 4; ks++)
            if ((ks >> 1) == part) {
#pragma unroll
                for (int i = 0; i < 4; i++)
                    asm volatile("ldmatrix.sync.aligned.m8n8.x4.trans.shared.b16 {%0,%1,%2,%3}, [%4];"
                                 : "=r"(af[i][ks][0]), "=r"(af[i][ks][1]), "=r"(af[i][ks][2]), "=r"(af[i][ks][3])
                                 : "r"(a_wo + ks * 2048 + (x_wo ^ (i << 5)))
                                 : "memory");
            }
    };
    load_wo(0);

    float o[8];
#pragma unroll
    for (int i = 0; i < 8; i++) o[i] = 0.f;
    float scale = 0.f;
    uint2 ml = make_uint2(0u, 0u);
    unsigned int* osend = pin(&g_obox[grp * 4 + (tid >> 6)][r][tid & 63]);
    unsigned int* asend = pin(&g_outbox[b * N_RED + (warp < 7 ? warp : 0) * 8 + (lane & 3) * 2][cta & 63][lane >> 2]);
    uint2* pml = pin(&g_mlbox[grp][lane]);
    const uint32_t a_ost = pin(ring + lane * 32);
    const uint32_t a_old = pin(sbase + SM_RING + tid * 4);
    const uint32_t a_ob = pin(sbase + SM_OB + (lane & 3) * 32);
    const uint32_t lane_p = pin((uint32_t)lane);
#pragma unroll 1
    for (int it = 0; it < NCH; it++) {
        if (it == NCH - 4) ml = box_ld64(pml);
        mbar_wait(fullb + s * (UPR * 8), ph);
        const uint32_t a = ring + s * (NW * SB) + lane * 16;
        uint4 pp[KPS / 4], v[KPS];
#pragma unroll
        for (int kg = 0; kg < KPS / 4; kg++) pp[kg] = lds128(sc + (it * KPS + kg * 4) * 4);
#pragma unroll
        for (int k = 0; k < KPS; k++) v[k] = lds128(a + k * 512);
        __syncwarp();
        if (elect_one()) mbar_arrive(fullb + NS * 8 + s * (UPR * 8));
#pragma unroll
        for (int k = 0; k < KPS; k++) {
            const uint4 p4 = pp[k >> 2];
            const float p = __uint_as_float((k & 3) == 0 ? p4.x : (k & 3) == 1 ? p4.y : (k & 3) == 2 ? p4.z : p4.w);
            o[0] = fmaf(bflo(v[k].x), p, o[0]);
            o[1] = fmaf(bfhi(v[k].x), p, o[1]);
            o[2] = fmaf(bflo(v[k].y), p, o[2]);
            o[3] = fmaf(bfhi(v[k].y), p, o[3]);
            o[4] = fmaf(bflo(v[k].z), p, o[4]);
            o[5] = fmaf(bfhi(v[k].z), p, o[5]);
            o[6] = fmaf(bflo(v[k].w), p, o[6]);
            o[7] = fmaf(bfhi(v[k].w), p, o[7]);
        }
        if (it == NCH - 2) {
            unsigned n = 0;
            while (__any_sync(0xffffffffu, ml.x == 0u || ml.y == 0u)) {
                if (ml.x == 0u || ml.y == 0u) ml = box_ld64(pml);
                if (++n > SPIN_LIMIT) __trap();
            }
            const float mi = __uint_as_float(ml.x), li = __uint_as_float(ml.y);
            float M = mi;
#pragma unroll
            for (int of = 16; of; of >>= 1) M = fmaxf(M, __shfl_xor_sync(0xffffffffu, M, of));
            float L = li * exp2f((mi - M) * LOG2E);
#pragma unroll
            for (int of = 16; of; of >>= 1) L += __shfl_xor_sync(0xffffffffu, L, of);
            scale = exp2f((m_w - M) * LOG2E) / L;
            if (r == 0) {
                box_st32(&g_qbox[grp][0][tid], 0u);
                box_st32(&g_qbox[grp][1][tid], 0u);
            }
        }
        if (++s == STAGES) { s = 0; ph ^= 1; }
    }

    sts128f(a_ost, o[0] * scale, o[1] * scale, o[2] * scale, o[3] * scale);
    sts128f(a_ost + 16, o[4] * scale, o[5] * scale, o[6] * scale, o[7] * scale);
    cta_sync();
    {
        float v[NW];
#pragma unroll
        for (int w = 0; w < NW; w++) v[w] = ldsf(a_old + w * SB);
        const float t = ((v[0] + v[1]) + (v[2] + v[3])) + ((v[4] + v[5]) + (v[6] + v[7]));
        box_st32(osend, box_enc(t));
    }
    if (warp == 7) return;
    load_wo(1);

    {
        asm volatile("bar.sync 3, 256;" ::: "memory");
        const uint4 bl = lds128(a_ob), bh = lds128(a_ob + 16);
        const uint32_t bf[8] = {bl.x, bl.y, bl.z, bl.w, bh.x, bh.y, bh.z, bh.w};
        float c[4][4];
#pragma unroll
        for (int i = 0; i < 4; i++) c[i][0] = c[i][1] = c[i][2] = c[i][3] = 0.f;
#pragma unroll
        for (int ks = 0; ks < 4; ks++)
#pragma unroll
            for (int i = 0; i < 4; i++)
                asm volatile("mma.sync.aligned.m16n8k16.row.col.f32.bf16.bf16.f32 {%0,%1,%2,%3}, {%4,%5,%6,%7}, {%8,%9}, {%0,%1,%2,%3};"
                             : "+f"(c[i][0]), "+f"(c[i][1]), "+f"(c[i][2]), "+f"(c[i][3])
                             : "r"(af[i][ks][0]), "r"(af[i][ks][1]), "r"(af[i][ks][2]), "r"(af[i][ks][3]),
                               "r"(bf[2 * ks]), "r"(bf[2 * ks + 1]));
        const uint32_t t = lane_p & 3;
        const float v0 = (t & 2) ? ((t & 1) ? c[3][0] : c[2][0]) : ((t & 1) ? c[1][0] : c[0][0]);
        const float v1 = (t & 2) ? ((t & 1) ? c[3][2] : c[2][2]) : ((t & 1) ? c[1][2] : c[0][2]);
        box_st32(asend, box_enc(v0));
        box_st32(asend + (64 + N_GLU) * 8, box_enc(v1));
    }
}

}

typedef CUresult (*PFN_tmapEncodeTiled)(CUtensorMap*, CUtensorMapDataType, cuuint32_t, void*, const cuuint64_t*,
                                        const cuuint64_t*, const cuuint32_t*, const cuuint32_t*, CUtensorMapInterleave,
                                        CUtensorMapSwizzle, CUtensorMapL2promotion, CUtensorMapFloatOOBfill);

extern "C" void kernel_launch(void* const* d_in, const int* in_sizes, int n_in, void* d_out, int out_size) {
    (void)in_sizes;
    (void)n_in;
    (void)out_size;
    const __nv_bfloat16* x = (const __nv_bfloat16*)d_in[0];
    const __nv_bfloat16* kc = (const __nv_bfloat16*)d_in[1];
    const __nv_bfloat16* vc = (const __nv_bfloat16*)d_in[2];
    const __nv_bfloat16* wg = (const __nv_bfloat16*)d_in[6];
    const __nv_bfloat16* wu = (const __nv_bfloat16*)d_in[7];
    const __nv_bfloat16* wd = (const __nv_bfloat16*)d_in[8];
    const __nv_bfloat16* gw = (const __nv_bfloat16*)d_in[9];
    static PFN_tmapEncodeTiled encode = nullptr;
    if (!encode) {
        cudaFuncSetAttribute(fused_decode_kernel, cudaFuncAttributeMaxDynamicSharedMemorySize, SM_TOTAL);
        void* fn = nullptr;
        cudaDriverEntryPointQueryResult qr;
        cudaGetDriverEntryPoint("cuTensorMapEncodeTiled", &fn, cudaEnableDefault, &qr);
        encode = (PFN_tmapEncodeTiled)fn;
        if (!encode) return;
    }
    CUtensorMap tm_wq;
    const cuuint64_t gdim[2] = {(cuuint64_t)kHD, (cuuint64_t)kD};
    const cuuint64_t gstride[1] = {(cuuint64_t)kHD * 2};
    const cuuint32_t box[2] = {64, 224};
    const cuuint32_t estr[2] = {1, 1};
    encode(&tm_wq, CU_TENSOR_MAP_DATA_TYPE_BFLOAT16, 2, d_in[3], gdim, gstride, box, estr, CU_TENSOR_MAP_INTERLEAVE_NONE,
           CU_TENSOR_MAP_SWIZZLE_NONE, CU_TENSOR_MAP_L2_PROMOTION_NONE, CU_TENSOR_MAP_FLOAT_OOB_FILL_NONE);
    CUtensorMap tm_wo;
    const cuuint64_t odim[2] = {(cuuint64_t)kD, (cuuint64_t)kHD};
    const cuuint64_t ostride[1] = {(cuuint64_t)kD * 2};
    const cuuint32_t obox[2] = {64, 32};
    encode(&tm_wo, CU_TENSOR_MAP_DATA_TYPE_BFLOAT16, 2, d_in[4], odim, ostride, obox, estr, CU_TENSOR_MAP_INTERLEAVE_NONE,
           CU_TENSOR_MAP_SWIZZLE_128B, CU_TENSOR_MAP_L2_PROMOTION_NONE, CU_TENSOR_MAP_FLOAT_OOB_FILL_NONE);
    __nv_bfloat16* outp = (__nv_bfloat16*)d_out;
    void* args[] = {&tm_wq, &tm_wo, &x, &kc, &vc, &wg, &wu, &wd, &gw, &outp};
    cudaLaunchCooperativeKernel((const void*)fused_decode_kernel, dim3(N_ATT + N_GLU), dim3(NT_LAUNCH), args, SM_TOTAL,
                                cudaStreamPerThread);
}
```
